```python
import torch

def _softmax(x, axis=-1):
    return torch.softmax(x, dim=axis)
def _gelu(x):
    return torch.nn.functional.gelu(x, approximate="tanh")
def _silu(x):
    return torch.nn.functional.silu(x)
def _sigmoid(x):
    return torch.sigmoid(x)
def _layernorm(x, axis=-1, eps=1e-5):
    m = x.mean(dim=axis, keepdim=True)
    v = x.var(dim=axis, keepdim=True, unbiased=False)
    return (x - m) / torch.sqrt(v + eps)
def _scatter_add(tgt, idx, src, axis=0):
    return tgt.clone().index_add_(axis, idx, src)
def _segment_sum(src, seg, n):
    out = torch.zeros((n,) + src.shape[1:], dtype=src.dtype)
    return out.index_add_(0, seg, src)
def _pad(x, pw):
    flat = tuple(v for pair in reversed(pw) for v in pair)
    return torch.nn.functional.pad(x, flat)

kernel_name = 'interleave_layers__gqa_block_cached__dense_activation_silu__decode'

def setup_inputs():

    _w = (lambda a: (lambda t: t.to(torch.bfloat16) if t.is_floating_point() else t)(torch.as_tensor(a)))
    def _A_setup():
        B, Sq, D = 8, 1, 512
        Hq, Hkv, Sk, Dh = 32, 8, 8192, 128
        assert Hq % Hkv == 0, (Hq, Hkv)
        return {
            "x": _w((lambda *s: torch.randn(*s, dtype=torch.bfloat16) * 0.1)(B, Sq, D)),
            "k_cache": _w((lambda *s: torch.randn(*s, dtype=torch.bfloat16) * 0.8)(B, Hkv, Sk, Dh)),
            "v_cache": _w((lambda *s: torch.randn(*s, dtype=torch.bfloat16) * 3.2)(B, Hkv, Sk, Dh)),
            "wq": _w((lambda *s: torch.randn(*s, dtype=torch.bfloat16) * 0.8)(D, Hq * Dh) * (D ** -0.5)),
            "wo": _w((lambda *s: torch.randn(*s, dtype=torch.bfloat16) * 3.2)(Hq * Dh, D) * ((Hq * Dh) ** -0.5)),
        }
    _A_in = _A_setup()

    def _B_setup():
        B, S, D, F = 8, 1, 512, 1792
        return {
            "x": _w((lambda *s: torch.randn(*s, dtype=torch.bfloat16) * 0.1)(B, S, D)),
            "w1": _w((lambda *s: torch.randn(*s, dtype=torch.bfloat16) * 1.6)(D, F) * (D ** -0.5)),
            "w2": _w((lambda *s: torch.randn(*s, dtype=torch.bfloat16) * 0.4)(F, D) * (F ** -0.5)),
        }
    _B_in = _B_setup()

    return {
        "A_x": _A_in["x"],
        "A_k_cache": _A_in["k_cache"],
        "A_v_cache": _A_in["v_cache"],
        "A_wq": _A_in["wq"],
        "A_wo": _A_in["wo"],
        "B_x": _B_in["x"],
        "B_w1": _B_in["w1"],
        "B_w2": _B_in["w2"],
    }

def reference(A_x, A_k_cache, A_v_cache, A_wq, A_wo, B_x, B_w1, B_w2):
    def _A_ref(x, k_cache, v_cache, wq, wo):
        B, Sq, D = x.shape
        Hq, Dh = 32, 128
        Hkv = k_cache.shape[1]
        rep = Hq // Hkv
        q = (lambda x, *d: x.permute(*d))((x @ wq).reshape(B, Sq, Hq, Dh), 0, 2, 1, 3)
        k = (lambda x, n, axis: torch.repeat_interleave(x, n, dim=axis))(k_cache, rep, axis=1)
        v = (lambda x, n, axis: torch.repeat_interleave(x, n, dim=axis))(v_cache, rep, axis=1)
        scores = torch.einsum("bhqd,bhkd->bhqk", q, k) * (Dh ** -0.5)
        p = _softmax(scores, axis=-1)
        o = torch.einsum("bhqk,bhkd->bhqd", p, v)
        return (lambda x, *d: x.permute(*d))(o, 0, 2, 1, 3).reshape(B, Sq, Hq * Dh) @ wo

    def _B_ref(x, w1, w2):
        h = torch.einsum("bsd,df->bsf", x, w1)
        h = _silu(h)
        out = torch.einsum("bsf,fd->bsd", h, w2)
        return out

    x = A_x
    x = x + _A_ref(_layernorm(x, axis=-1), A_k_cache, A_v_cache, A_wq, A_wo)
    x = x + _B_ref(_layernorm(x, axis=-1), B_w1, B_w2)
    x = x + _A_ref(_layernorm(x, axis=-1), A_k_cache, A_v_cache, A_wq, A_wo)
    x = x + _B_ref(_layernorm(x, axis=-1), B_w1, B_w2)
    return x
```

```cpp
#include <cuda_runtime.h>
#include <cuda.h>
#include <cuda_bf16.h>
#include <stdint.h>

namespace {

constexpr int NB = 8;
constexpr int NT = 16;
constexpr int TK = 32;
constexpr int NSLOT = 13;
constexpr int RMAX = 10;
constexpr int HALF_BYTES = TK * 256;
constexpr int TILE_BYTES = 2 * HALF_BYTES;
constexpr int PART_STRIDE = 528;
constexpr int NTHREADS = 512;
constexpr int NW1 = 2;
constexpr int NW2 = 4;
constexpr float SCALE_LOG2 = 0.08838834764831845f * 1.4426950408889634f;
constexpr unsigned SPIN_LIMIT = 1u << 24;

constexpr int OFF_MB1 = NSLOT * TILE_BYTES;
constexpr int OFF_MB2 = OFF_MB1 + 2048;
constexpr int OFF_ML1 = OFF_MB2 + 6144;
constexpr int OFF_ML2 = OFF_ML1 + 128;
constexpr int OFF_XS = OFF_ML2 + 128;
constexpr int OFF_RED0 = OFF_XS + 2048;
constexpr int OFF_RED1 = OFF_RED0 + 2048;
constexpr int OFF_STAT = OFF_RED1 + 1024;
constexpr int OFF_BAR = OFF_STAT + 64;
constexpr int OFF_INFO = OFF_BAR + 768;
constexpr int OFF_MISC = OFF_INFO + 256;
constexpr int SMEM_BYTES = OFF_MISC + 16;
constexpr int BAR_FULLD = 0, BAR_FULLL = 32, BAR_P1DONE = 64, BAR_P2DONE = 72, BAR_QGO = 80, BAR_LGO = 88;

__device__ __align__(16) float g_part[2][NB][128][PART_STRIDE];
__device__ __align__(16) float g_y[NB + 1][2][8][512];
__device__ __align__(16) float g_h[NB + 1][2][1792];
__device__ __align__(16) float g_z[NB + 1][2][4][512];
__device__ __align__(16) float g_q[2][NB][8][512];
__device__ unsigned g_epoch;

__device__ __forceinline__ uint32_t smem_u32(const void* p) { return (uint32_t)__cvta_generic_to_shared(p); }
__device__ __forceinline__ void mbar_init(uint32_t bar, uint32_t cnt) {
  asm volatile("mbarrier.init.shared::cta.b64 [%0], %1;" ::"r"(bar), "r"(cnt));
}
__device__ __forceinline__ void mbar_arrive(uint32_t bar) {
  asm volatile("mbarrier.arrive.shared::cta.b64 _, [%0];" ::"r"(bar) : "memory");
}
__device__ __forceinline__ void mbar_expect_tx(uint32_t bar, uint32_t bytes) {
  asm volatile("mbarrier.arrive.expect_tx.shared::cta.b64 _, [%0], %1;" ::"r"(bar), "r"(bytes) : "memory");
}
__device__ __forceinline__ void mbar_wait(uint32_t bar, uint32_t parity) {
  uint32_t ok, it = 0;
  do {
    asm volatile(
        "{\n.reg .pred p;\nmbarrier.try_wait.parity.shared::cta.b64 p, [%1], %2;\nselp.u32 %0, 1, 0, p;\n}"
        : "=r"(ok)
        : "r"(bar), "r"(parity)
        : "memory");
    if (++it > SPIN_LIMIT) __trap();
  } while (!ok);
}
__device__ __forceinline__ bool mbar_test(uint32_t bar, uint32_t parity) {
  uint32_t ok;
  asm volatile(
      "{\n.reg .pred p;\nmbarrier.test_wait.parity.shared::cta.b64 p, [%1], %2;\nselp.u32 %0, 1, 0, p;\n}"
      : "=r"(ok)
      : "r"(bar), "r"(parity)
      : "memory");
  return ok;
}
__device__ __forceinline__ void tma3d(uint32_t dst, const CUtensorMap* tm, int row, uint32_t bar, uint64_t pol) {
  asm volatile(
      "cp.async.bulk.tensor.3d.shared::cluster.global.mbarrier::complete_tx::bytes.L2::cache_hint "
      "[%0], [%1, {%3, %4, %3}], [%2], %5;" ::"r"(dst),
      "l"((uint64_t)tm), "r"(bar), "r"(0), "r"(row), "l"(pol)
      : "memory");
}
__device__ __forceinline__ void l2_prefetch(const void* p, uint32_t bytes) {
  asm volatile("cp.async.bulk.prefetch.L2.global [%0], %1;" ::"l"(p), "r"(bytes) : "memory");
}
__device__ __forceinline__ void release_slot(uint32_t freeaddr, uint32_t bits) {
  asm volatile("red.release.cta.shared::cta.or.b32 [%0], %1;" ::"r"(freeaddr), "r"(bits) : "memory");
}
__device__ __forceinline__ uint32_t grab_free(uint32_t freeaddr) {
  uint32_t v;
  asm volatile("atom.acquire.cta.shared::cta.exch.b32 %0, [%1], 0;" : "=r"(v) : "r"(freeaddr) : "memory");
  return v;
}
__device__ __forceinline__ void bar_sync(int id, int n) { asm volatile("bar.sync %0, %1;" ::"r"(id), "r"(n) : "memory"); }
__device__ __forceinline__ void mma16816(float (&d)[4], uint32_t a0, uint32_t a1, uint32_t a2, uint32_t a3, uint32_t b0,
                                         uint32_t b1) {
  asm("mma.sync.aligned.m16n8k16.row.col.f32.bf16.bf16.f32 {%0,%1,%2,%3}, {%4,%5,%6,%7}, {%8,%9}, {%0,%1,%2,%3};"
      : "+f"(d[0]), "+f"(d[1]), "+f"(d[2]), "+f"(d[3])
      : "r"(a0), "r"(a1), "r"(a2), "r"(a3), "r"(b0), "r"(b1));
}
__device__ __forceinline__ void ldsm4(uint32_t (&r)[4], uint32_t addr) {
  asm volatile("ldmatrix.sync.aligned.m8n8.x4.shared.b16 {%0,%1,%2,%3}, [%4];"
               : "=r"(r[0]), "=r"(r[1]), "=r"(r[2]), "=r"(r[3])
               : "r"(addr)
               : "memory");
}
__device__ __forceinline__ void ldsm4t(uint32_t (&r)[4], uint32_t addr) {
  asm volatile("ldmatrix.sync.aligned.m8n8.x4.trans.shared.b16 {%0,%1,%2,%3}, [%4];"
               : "=r"(r[0]), "=r"(r[1]), "=r"(r[2]), "=r"(r[3])
               : "r"(addr)
               : "memory");
}
__device__ __forceinline__ uint32_t movm(uint32_t a) {
  uint32_t d;
  asm volatile("movmatrix.sync.aligned.m8n8.trans.b16 %0, %1;" : "=r"(d) : "r"(a));
  return d;
}
__device__ __forceinline__ uint32_t pack_bf16(float lo, float hi) {
  uint32_t d;
  asm("cvt.rn.bf16x2.f32 %0, %1, %2;" : "=r"(d) : "f"(hi), "f"(lo));
  return d;
}
__device__ __forceinline__ float rbf(float x) { return __bfloat162float(__float2bfloat16_rn(x)); }
__device__ __forceinline__ float bf_lo(uint32_t v) { return __uint_as_float(v << 16); }
__device__ __forceinline__ float bf_hi(uint32_t v) { return __uint_as_float(v & 0xffff0000u); }
__device__ __forceinline__ float ex2(float x) {
  float y;
  asm("ex2.approx.ftz.f32 %0, %1;" : "=f"(y) : "f"(x));
  return y;
}
__device__ __forceinline__ uint4 ld_rlx4(const float* p) {
  uint4 v;
  asm volatile("ld.relaxed.gpu.global.v4.u32 {%0,%1,%2,%3}, [%4];"
               : "=r"(v.x), "=r"(v.y), "=r"(v.z), "=r"(v.w)
               : "l"(p)
               : "memory");
  return v;
}
__device__ __forceinline__ uint2 ld_rlx2(const float* p) {
  uint2 v;
  asm volatile("ld.relaxed.gpu.global.v2.u32 {%0,%1}, [%2];" : "=r"(v.x), "=r"(v.y) : "l"(p) : "memory");
  return v;
}
__device__ __forceinline__ uint32_t tagw(float f, uint32_t tag) { return (__float_as_uint(f) & ~1u) | tag; }
__device__ __forceinline__ void st_rlx1(float* p, float v, uint32_t tag) {
  asm volatile("st.relaxed.gpu.global.u32 [%0], %1;" ::"l"(p), "r"(tagw(v, tag)) : "memory");
}
__device__ __forceinline__ void st_rlx2(float* p, float a, float b, uint32_t tag) {
  asm volatile("st.relaxed.gpu.global.v2.u32 [%0], {%1,%2};" ::"l"(p), "r"(tagw(a, tag)), "r"(tagw(b, tag)) : "memory");
}
__device__ __forceinline__ uint32_t bad4(const uint4& v, uint32_t tag) {
  return (v.x ^ tag) | (v.y ^ tag) | (v.z ^ tag) | (v.w ^ tag);
}
__device__ __forceinline__ float u2f(uint32_t u) { return __uint_as_float(u); }
__device__ __forceinline__ void sel_if(float& o, float v, int a, int b) {
  asm("{\n.reg .pred p;\nsetp.eq.s32 p, %2, %3;\nselp.f32 %0, %1, %0, p;\n}" : "+f"(o) : "f"(v), "r"(a), "r"(b));
}

__device__ __forceinline__ void warp_stats(float& mean, float& m2, float cnt) {
#pragma unroll
  for (int o = 1; o < 32; o <<= 1) {
    float mb = __shfl_xor_sync(0xffffffffu, mean, o);
    float qb = __shfl_xor_sync(0xffffffffu, m2, o);
    float d = mb - mean;
    mean = 0.5f * (mean + mb);
    m2 = m2 + qb + d * d * (0.5f * cnt);
    cnt *= 2.f;
  }
}
__device__ __forceinline__ void ln_consts(float mean, float m2, float& mb, float& den) {
  mb = rbf(mean);
  float v = rbf(m2 * (1.f / 512.f));
  den = rbf(sqrtf(rbf(v + 1e-5f)));
}
__device__ __forceinline__ float ln_apply(float x, float mb, float den) { return __fdividef(rbf(x - mb), den); }

struct AttnState {
  float acc[8][4];
  float m0, m1, l0, l1;
};

__device__ __forceinline__ void process_tile(uint32_t slot_addr, uint32_t kb, uint32_t vb, const uint32_t (&qf)[8][2],
                                             AttnState& st) {
  float s[2][2][4];
#pragma unroll
  for (int kg = 0; kg < 2; kg++)
#pragma unroll
    for (int h = 0; h < 2; h++)
#pragma unroll
      for (int i = 0; i < 4; i++) s[kg][h][i] = 0.f;
#pragma unroll
  for (int kk = 0; kk < 8; kk++) {
#pragma unroll
    for (int kg = 0; kg < 2; kg++) {
      uint32_t a[4];
      ldsm4(a, slot_addr + (kb ^ ((kk & 3) << 5)) + (kk >> 2) * 4096 + kg * 2048);
      mma16816(s[kg][kk & 1], a[0], a[1], a[2], a[3], qf[kk][0], qf[kk][1]);
    }
  }
  float sv[2][4];
#pragma unroll
  for (int kg = 0; kg < 2; kg++)
#pragma unroll
    for (int i = 0; i < 4; i++) sv[kg][i] = s[kg][0][i] + s[kg][1][i];
  float t0 = fmaxf(fmaxf(sv[0][0], sv[0][2]), fmaxf(sv[1][0], sv[1][2]));
  float t1 = fmaxf(fmaxf(sv[0][1], sv[0][3]), fmaxf(sv[1][1], sv[1][3]));
#pragma unroll
  for (int o = 4; o < 32; o <<= 1) {
    t0 = fmaxf(t0, __shfl_xor_sync(0xffffffffu, t0, o));
    t1 = fmaxf(t1, __shfl_xor_sync(0xffffffffu, t1, o));
  }
  if (__any_sync(0xffffffffu, (t0 > st.m0) || (t1 > st.m1))) {
    float n0 = fmaxf(st.m0, t0), n1 = fmaxf(st.m1, t1);
    float a0 = ex2((st.m0 - n0) * SCALE_LOG2), a1 = ex2((st.m1 - n1) * SCALE_LOG2);
    st.m0 = n0;
    st.m1 = n1;
    st.l0 *= a0;
    st.l1 *= a1;
#pragma unroll
    for (int mt = 0; mt < 8; mt++) {
      st.acc[mt][0] *= a0;
      st.acc[mt][1] *= a1;
      st.acc[mt][2] *= a0;
      st.acc[mt][3] *= a1;
    }
  }
  const float c0 = -st.m0 * SCALE_LOG2, c1 = -st.m1 * SCALE_LOG2;
  uint32_t pb[2][2];
#pragma unroll
  for (int kg = 0; kg < 2; kg++) {
    float p0 = ex2(fmaf(sv[kg][0], SCALE_LOG2, c0));
    float p1 = ex2(fmaf(sv[kg][1], SCALE_LOG2, c1));
    float p2 = ex2(fmaf(sv[kg][2], SCALE_LOG2, c0));
    float p3 = ex2(fmaf(sv[kg][3], SCALE_LOG2, c1));
    st.l0 += p0 + p2;
    st.l1 += p1 + p3;
    pb[kg][0] = movm(pack_bf16(p0, p1));
    pb[kg][1] = movm(pack_bf16(p2, p3));
  }
#pragma unroll
  for (int kg = 0; kg < 2; kg++) {
#pragma unroll
    for (int mt = 0; mt < 8; mt++) {
      uint32_t a[4];
      ldsm4t(a, slot_addr + (vb ^ ((mt & 3) << 5)) + (mt >> 2) * 4096 + kg * 2048);
      mma16816(st.acc[mt], a[0], a[1], a[2], a[3], pb[kg][0], pb[kg][1]);
    }
  }
}

template <int LAYER, int NW>
__device__ __forceinline__ void attn_role(char* smem, int w, int lane, int cta, uint32_t tag) {
  const uint32_t sbase = smem_u32(smem);
  const uint32_t bars = sbase + OFF_BAR;
  const uint32_t freeaddr = sbase + OFF_MISC;
  volatile uint8_t* info = (volatile uint8_t*)(smem + OFF_INFO);
  volatile uint8_t* linfo = info + NB * NT;
  float* mbuf = (float*)(smem + (LAYER ? OFF_MB2 : OFF_MB1));
  float* mlbuf = (float*)(smem + (LAYER ? OFF_ML2 : OFF_ML1));
  const int g = cta >> 4;
  const int g8 = lane >> 2, j = lane & 3;
  const uint32_t x7 = lane & 7;
  const uint32_t kb = (x7 + 8 * ((lane >> 3) & 1)) * 128 + ((((uint32_t)lane >> 4) ^ x7) << 4);
  const uint32_t vb = (x7 + 8 * (lane >> 4)) * 128 + (((((uint32_t)lane >> 3) & 1) ^ x7) << 4) + HALF_BYTES;
  uint32_t lpar = 0;

#pragma unroll 1
  for (int b = 0; b < NB; b++) {
    uint32_t qf[8][2];
    {
      if (LAYER == 1) mbar_wait(bars + 8 * (BAR_QGO + b), 0);
      const float* qp = &g_q[LAYER][b][g][(g8 & 3) * 128 + (g8 >> 2) * 64 + j * 16];
      uint4 v[4];
      uint32_t it = 0;
      while (true) {
#pragma unroll
        for (int u = 0; u < 4; u++) v[u] = ld_rlx4(qp + 4 * u);
        uint32_t bad = bad4(v[0], tag) | bad4(v[1], tag) | bad4(v[2], tag) | bad4(v[3], tag);
        if (!(bad & 1)) break;
        if (++it > SPIN_LIMIT) __trap();
      }
      __syncwarp();
#pragma unroll
      for (int u = 0; u < 4; u++) {
        uint32_t r0 = __byte_perm(v[u].x, v[u].y, 0x7632);
        uint32_t r1 = __byte_perm(v[u].z, v[u].w, 0x7632);
        uint32_t o0 = __shfl_down_sync(0xffffffffu, r0, 16);
        uint32_t o1 = __shfl_down_sync(0xffffffffu, r1, 16);
        bool lo = lane < 16;
        qf[u][0] = lo ? r0 : 0u;
        qf[u][1] = lo ? r1 : 0u;
        qf[4 + u][0] = lo ? o0 : 0u;
        qf[4 + u][1] = lo ? o1 : 0u;
      }
    }
    AttnState st;
#pragma unroll
    for (int mt = 0; mt < 8; mt++)
#pragma unroll
      for (int i = 0; i < 4; i++) st.acc[mt][i] = 0.f;
    st.m0 = st.m1 = -INFINITY;
    st.l0 = st.l1 = 0.f;

    if (LAYER == 0) {
#pragma unroll 1
      for (int t = w; t < NT; t += NW) {
        mbar_wait(bars + 8 * (BAR_FULLD + (b & 1) * NT + t), (b >> 1) & 1);
        uint32_t inf = info[b * NT + t];
        uint32_t slot = inf & 0x7f;
        process_tile(sbase + slot * TILE_BYTES, kb, vb, qf, st);
        __syncwarp();
        if (!(inf & 0x80) && lane == 0) release_slot(freeaddr, 1u << slot);
      }
    } else {
#pragma unroll 1
      for (int i = 0; i < 2 * (NT / NW); i++) {
        int t = w + NW * (i % (NT / NW));
        uint32_t inf = info[b * NT + t];
        bool ret = inf & 0x80;
        if (ret != (i < NT / NW)) continue;
        uint32_t slot = inf & 0x7f;
        if (!ret) {
          int bi = (b & 1) * NT + t;
          mbar_wait(bars + 8 * (BAR_FULLL + bi), (lpar >> bi) & 1);
          lpar ^= 1u << bi;
          slot = linfo[b * NT + t];
        }
        process_tile(sbase + slot * TILE_BYTES, kb, vb, qf, st);
        __syncwarp();
        if (lane == 0) release_slot(freeaddr, 1u << slot);
      }
    }

    constexpr int OWN = 8 / NW;
#pragma unroll
    for (int o = 4; o < 32; o <<= 1) {
      st.l0 += __shfl_xor_sync(0xffffffffu, st.l0, o);
      st.l1 += __shfl_xor_sync(0xffffffffu, st.l1, o);
    }
    if (lane < 2) *(float4*)&mlbuf[w * 8 + lane * 4] = make_float4(st.m0, st.l0, st.m1, st.l1);
    if (j < 2) {
#pragma unroll
      for (int mt = 0; mt < 8; mt++) {
        int ow = mt / OWN;
        if (ow != w) {
          int sr = (w - ow - 1) & (NW - 1);
          *(float4*)&mbuf[(((ow * (NW - 1) + sr) * OWN + (mt % OWN)) * 16 + g8 * 2 + j) * 4] =
              make_float4(st.acc[mt][0], st.acc[mt][1], st.acc[mt][2], st.acc[mt][3]);
        }
      }
    }
    bar_sync(2 + LAYER, 32 * NW);
    if (j < 2) {
      float4 mlv[NW];
#pragma unroll
      for (int u = 0; u < NW; u++) mlv[u] = *(const float4*)&mlbuf[((w + u) & (NW - 1)) * 8 + j * 4];
      float M0 = mlv[0].x, M1 = mlv[0].z;
#pragma unroll
      for (int u = 1; u < NW; u++) {
        M0 = fmaxf(M0, mlv[u].x);
        M1 = fmaxf(M1, mlv[u].z);
      }
      float f0[NW], f1[NW], L0 = 0.f, L1 = 0.f;
#pragma unroll
      for (int u = 0; u < NW; u++) {
        f0[u] = ex2((mlv[u].x - M0) * SCALE_LOG2);
        f1[u] = ex2((mlv[u].z - M1) * SCALE_LOG2);
        L0 = fmaf(f0[u], mlv[u].y, L0);
        L1 = fmaf(f1[u], mlv[u].w, L1);
      }
      float* pp = &g_part[LAYER][b][cta][0];
#pragma unroll
      for (int e = 0; e < OWN; e++) {
        float o0 = 0.f, o1 = 0.f, o2 = 0.f, o3 = 0.f;
#pragma unroll
        for (int cw = 0; cw < NW; cw++) {
          sel_if(o0, st.acc[OWN * cw + e][0], w, cw);
          sel_if(o1, st.acc[OWN * cw + e][1], w, cw);
          sel_if(o2, st.acc[OWN * cw + e][2], w, cw);
          sel_if(o3, st.acc[OWN * cw + e][3], w, cw);
        }
        o0 *= f0[0];
        o1 *= f1[0];
        o2 *= f0[0];
        o3 *= f1[0];
#pragma unroll
        for (int sr = 0; sr < NW - 1; sr++) {
          float4 a = *(const float4*)&mbuf[(((w * (NW - 1) + sr) * OWN + e) * 16 + g8 * 2 + j) * 4];
          o0 = fmaf(a.x, f0[sr + 1], o0);
          o1 = fmaf(a.y, f1[sr + 1], o1);
          o2 = fmaf(a.z, f0[sr + 1], o2);
          o3 = fmaf(a.w, f1[sr + 1], o3);
        }
        int mt = OWN * w + e;
        st_rlx2(pp + (2 * j) * 128 + mt * 16 + 2 * g8, o0, o2, tag);
        st_rlx2(pp + (2 * j + 1) * 128 + mt * 16 + 2 * g8, o1, o3, tag);
      }
      if (w == 0 && g8 == 0) {
        st_rlx2(pp + 512 + 4 * j, M0, L0, tag);
        st_rlx2(pp + 512 + 4 * j + 2, M1, L1, tag);
      }
    }
    __syncwarp();
    if (lane == 0) mbar_arrive(bars + 8 * ((LAYER ? BAR_P2DONE : BAR_P1DONE) + b));
    bar_sync(2 + LAYER, 32 * NW);
  }
}

__device__ __forceinline__ void combine(const float* part  , int g, int w, int lane, uint32_t tag,
                                        uint32_t& r0, uint32_t& r1) {
  const int i = lane & 15, sh = lane >> 4, hh = w >> 1;
  const float* base = part + (size_t)(16 * g + 8 * sh) * PART_STRIDE;
  const float* po = base + 64 * w + 4 * i;
  const float* pm = base + 512 + 2 * hh;
  uint4 o4[8];
  uint2 ml[8];
  uint32_t it = 0;
  while (true) {
    uint32_t bad = 0;
#pragma unroll
    for (int u = 0; u < 8; u++) {
      o4[u] = ld_rlx4(po + u * PART_STRIDE);
      ml[u] = ld_rlx2(pm + u * PART_STRIDE);
    }
#pragma unroll
    for (int u = 0; u < 8; u++) bad |= bad4(o4[u], tag) | (ml[u].x ^ tag) | (ml[u].y ^ tag);
    if (!(bad & 1)) break;
    if (++it > SPIN_LIMIT) __trap();
  }
  __syncwarp();
  float M = u2f(ml[0].x);
#pragma unroll
  for (int u = 1; u < 8; u++) M = fmaxf(M, u2f(ml[u].x));
  M = fmaxf(M, __shfl_xor_sync(0xffffffffu, M, 16));
  float L = 0.f, a0 = 0.f, a1 = 0.f, a2 = 0.f, a3 = 0.f;
#pragma unroll
  for (int u = 0; u < 8; u++) {
    float f = ex2((u2f(ml[u].x) - M) * SCALE_LOG2);
    L = fmaf(f, u2f(ml[u].y), L);
    a0 = fmaf(f, u2f(o4[u].x), a0);
    a1 = fmaf(f, u2f(o4[u].y), a1);
    a2 = fmaf(f, u2f(o4[u].z), a2);
    a3 = fmaf(f, u2f(o4[u].w), a3);
  }
  L += __shfl_xor_sync(0xffffffffu, L, 16);
  a0 += __shfl_xor_sync(0xffffffffu, a0, 16);
  a1 += __shfl_xor_sync(0xffffffffu, a1, 16);
  a2 += __shfl_xor_sync(0xffffffffu, a2, 16);
  a3 += __shfl_xor_sync(0xffffffffu, a3, 16);
  float inv = 1.f / L;
  r0 = pack_bf16(a0 * inv, a1 * inv);
  r1 = pack_bf16(a2 * inv, a3 * inv);
}

__device__ __forceinline__ int q_pos(int c) {
  int hh = c >> 7, d = c & 127;
  int kk = d >> 4, r = d & 15;
  int jj = (r & 7) >> 1, e = (r & 1) + 2 * (r >> 3);
  return hh * 128 + (kk >> 2) * 64 + jj * 16 + (kk & 3) * 4 + e;
}

__device__ __forceinline__ void chain_role(char* smem, int tid, int cta, uint32_t tag, const __nv_bfloat16* __restrict__ x,
                                           const __nv_bfloat16* __restrict__ wq, const __nv_bfloat16* __restrict__ wo,
                                           const __nv_bfloat16* __restrict__ w1, const __nv_bfloat16* __restrict__ w2,
                                           __nv_bfloat16* __restrict__ out) {
  const uint32_t sbase = smem_u32(smem);
  const uint32_t bars = sbase + OFF_BAR;
  const int w = tid >> 5, lane = tid & 31, g8 = lane >> 2, j = lane & 3;
  const int g = cta >> 4, s = cta & 15;
  const int cg = cta & 31, kq = cta >> 5;
  __nv_bfloat16* xs = (__nv_bfloat16*)(smem + OFF_XS);
  float* red0 = (float*)(smem + OFF_RED0);
  float* red1 = (float*)(smem + OFF_RED1);
  float* stat = (float*)(smem + OFF_STAT);

  uint32_t fq[4][2][4], fo[4][2][4], f1[4][4], f2[4][4];

  {
    const __nv_bfloat16* p = wq + (size_t)(64 * w + 4 * j) * 4096 + 512 * g + 32 * s + 4 * g8;
    uint2 r[4][4];
#pragma unroll
    for (int ks = 0; ks < 4; ks++)
#pragma unroll
      for (int e = 0; e < 4; e++) r[ks][e] = __ldg((const uint2*)(p + (size_t)(16 * ks + e) * 4096));
    {
      const uint4* xp = (const uint4*)(x + w * 512 + lane * 16);
      uint4 a = __ldg(xp), c = __ldg(xp + 1);
      uint32_t xv[8] = {a.x, a.y, a.z, a.w, c.x, c.y, c.z, c.w};
      float f[16];
#pragma unroll
      for (int u = 0; u < 8; u++) {
        f[2 * u] = bf_lo(xv[u]);
        f[2 * u + 1] = bf_hi(xv[u]);
      }
      float mean = 0.f;
#pragma unroll
      for (int u = 0; u < 16; u++) mean += f[u];
      mean *= (1.f / 16.f);
      float m2 = 0.f;
#pragma unroll
      for (int u = 0; u < 16; u++) m2 = fmaf(f[u] - mean, f[u] - mean, m2);
      warp_stats(mean, m2, 16.f);
      float mb, den;
      ln_consts(mean, m2, mb, den);
      uint32_t o[8];
#pragma unroll
      for (int u = 0; u < 8; u++) o[u] = pack_bf16(ln_apply(f[2 * u], mb, den), ln_apply(f[2 * u + 1], mb, den));
      uint4* xn = (uint4*)(smem + OFF_MB1 + (w * 512 + lane * 16) * 2);
      xn[0] = make_uint4(o[0], o[1], o[2], o[3]);
      xn[1] = make_uint4(o[4], o[5], o[6], o[7]);
    }
#pragma unroll
    for (int ks = 0; ks < 4; ks++) {
      fq[ks][0][0] = __byte_perm(r[ks][0].x, r[ks][1].x, 0x5410);
      fq[ks][0][1] = __byte_perm(r[ks][0].x, r[ks][1].x, 0x7632);
      fq[ks][0][2] = __byte_perm(r[ks][2].x, r[ks][3].x, 0x5410);
      fq[ks][0][3] = __byte_perm(r[ks][2].x, r[ks][3].x, 0x7632);
      fq[ks][1][0] = __byte_perm(r[ks][0].y, r[ks][1].y, 0x5410);
      fq[ks][1][1] = __byte_perm(r[ks][0].y, r[ks][1].y, 0x7632);
      fq[ks][1][2] = __byte_perm(r[ks][2].y, r[ks][3].y, 0x5410);
      fq[ks][1][3] = __byte_perm(r[ks][2].y, r[ks][3].y, 0x7632);
    }
  }
  bar_sync(1, 256);
  {
    float c[2][4] = {{0.f, 0.f, 0.f, 0.f}, {0.f, 0.f, 0.f, 0.f}};
#pragma unroll
    for (int ks = 0; ks < 4; ks++) {
      uint2 bv = *(const uint2*)(smem + OFF_MB1 + (g8 * 512 + 64 * w + 16 * ks + 4 * j) * 2);
      mma16816(c[0], fq[ks][0][0], fq[ks][0][1], fq[ks][0][2], fq[ks][0][3], bv.x, bv.y);
      mma16816(c[1], fq[ks][1][0], fq[ks][1][1], fq[ks][1][2], fq[ks][1][3], bv.x, bv.y);
    }
    bar_sync(1, 256);
    float* rb = (float*)(smem + OFF_MB1);
#pragma unroll
    for (int mt = 0; mt < 2; mt++) {
      *(float2*)&rb[(w * 32 + 4 * g8 + 2 * mt) * 8 + 2 * j] = make_float2(c[mt][0], c[mt][1]);
      *(float2*)&rb[(w * 32 + 4 * g8 + 2 * mt + 1) * 8 + 2 * j] = make_float2(c[mt][2], c[mt][3]);
    }
    bar_sync(1, 256);
    float sum = 0.f;
#pragma unroll
    for (int u = 0; u < 8; u++) sum += rb[u * 256 + tid];
    int col = tid >> 3, n = tid & 7;
    st_rlx1(&g_q[0][n][g][q_pos(32 * s + col)], rbf(sum), tag);
  }
  {
    uint2 r[4][4];
#pragma unroll
    for (int ks = 0; ks < 4; ks++)
#pragma unroll
      for (int e = 0; e < 4; e++) {
        int p = 64 * w + 16 * ks + 4 * j + e;
        int hh = p >> 7, pp = p & 127;
        int dim = (pp & ~15) + ((pp & 15) >> 1) + 8 * (pp & 1);
        r[ks][e] = __ldg((const uint2*)(wo + (size_t)(512 * g + 128 * hh + dim) * 512 + 32 * s + 4 * g8));
      }
    uint32_t r1[4][4], r2[4][4];
#pragma unroll
    for (int ks = 0; ks < 4; ks++)
#pragma unroll
      for (int e = 0; e < 4; e++) {
        int k = 64 * w + 16 * ks + 4 * j + e;
        r1[ks][e] = cta < 112 ? __ldg((const uint32_t*)(w1 + (size_t)k * 1792 + 16 * cta + 2 * g8)) : 0u;
        r2[ks][e] = w < 7 ? __ldg((const uint32_t*)(w2 + (size_t)(448 * kq + k) * 512 + 16 * cg + 2 * g8)) : 0u;
      }
#pragma unroll
    for (int ks = 0; ks < 4; ks++) {
      fo[ks][0][0] = __byte_perm(r[ks][0].x, r[ks][1].x, 0x5410);
      fo[ks][0][1] = __byte_perm(r[ks][0].x, r[ks][1].x, 0x7632);
      fo[ks][0][2] = __byte_perm(r[ks][2].x, r[ks][3].x, 0x5410);
      fo[ks][0][3] = __byte_perm(r[ks][2].x, r[ks][3].x, 0x7632);
      fo[ks][1][0] = __byte_perm(r[ks][0].y, r[ks][1].y, 0x5410);
      fo[ks][1][1] = __byte_perm(r[ks][0].y, r[ks][1].y, 0x7632);
      fo[ks][1][2] = __byte_perm(r[ks][2].y, r[ks][3].y, 0x5410);
      fo[ks][1][3] = __byte_perm(r[ks][2].y, r[ks][3].y, 0x7632);
      f1[ks][0] = __byte_perm(r1[ks][0], r1[ks][1], 0x5410);
      f1[ks][1] = __byte_perm(r1[ks][0], r1[ks][1], 0x7632);
      f1[ks][2] = __byte_perm(r1[ks][2], r1[ks][3], 0x5410);
      f1[ks][3] = __byte_perm(r1[ks][2], r1[ks][3], 0x7632);
      f2[ks][0] = __byte_perm(r2[ks][0], r2[ks][1], 0x5410);
      f2[ks][1] = __byte_perm(r2[ks][0], r2[ks][1], 0x7632);
      f2[ks][2] = __byte_perm(r2[ks][2], r2[ks][3], 0x5410);
      f2[ks][3] = __byte_perm(r2[ks][2], r2[ks][3], 0x7632);
    }
  }

  const int n = tid >> 7, quad = tid & 127;

#pragma unroll 1
  for (int c = 0; c <= NB; c++) {
    const bool has_mid = c < NB, has_post = c > 0;
    __nv_bfloat16* xmid = xs + (c & 1) * 512;
    __nv_bfloat16* xpost = xs + ((c + 1) & 1) * 512;
    {
      uint32_t p0 = 0, p1 = 0, m0 = 0, m1 = 0;
      if (has_post) {
        mbar_wait(bars + 8 * (BAR_P2DONE + c - 1), 0);
        combine(&g_part[1][c - 1][0][0], g, w, lane, tag, p0, p1);
      }
      if (has_mid) {
        mbar_wait(bars + 8 * (BAR_P1DONE + c), 0);
        combine(&g_part[0][c][0][0], g, w, lane, tag, m0, m1);
      }
      uint32_t s0 = lane < 16 ? m0 : p0, s1 = lane < 16 ? m1 : p1;
      float acc[2][4] = {{0.f, 0.f, 0.f, 0.f}, {0.f, 0.f, 0.f, 0.f}};
#pragma unroll
      for (int ks = 0; ks < 4; ks++) {
        int src = (g8 & 1) * 16 + 4 * ks + j;
        uint32_t b0 = __shfl_sync(0xffffffffu, s0, src), b1 = __shfl_sync(0xffffffffu, s1, src);
        mma16816(acc[0], fo[ks][0][0], fo[ks][0][1], fo[ks][0][2], fo[ks][0][3], b0, b1);
        mma16816(acc[1], fo[ks][1][0], fo[ks][1][1], fo[ks][1][2], fo[ks][1][3], b0, b1);
      }
      if (j == 0) {
        *(float4*)&red0[w * 64 + 4 * g8] = make_float4(acc[0][0], acc[0][2], acc[1][0], acc[1][2]);
        *(float4*)&red0[w * 64 + 32 + 4 * g8] = make_float4(acc[0][1], acc[0][3], acc[1][1], acc[1][3]);
      }
      bar_sync(1, 256);
      if (tid < 64) {
        float sum = 0.f;
#pragma unroll
        for (int u = 0; u < 8; u++) sum += red0[u * 64 + tid];
        st_rlx1(&g_y[c][tid >> 5][g][32 * s + (tid & 31)], sum, tag);
      }
    }
    {
      uint2 bs = make_uint2(0u, 0u);
      if (n == 0) {
        if (has_mid) bs = __ldg((const uint2*)(x + c * 512 + 4 * quad));
      } else if (has_post) {
        bs = *(const uint2*)(xpost + 4 * quad);
      }
      const float* yp = &g_y[c][n][0][4 * quad];
      uint4 v[8];
      uint32_t it = 0;
      while (true) {
        uint32_t bad = 0;
#pragma unroll
        for (int u = 0; u < 8; u++) v[u] = ld_rlx4(yp + u * 512);
#pragma unroll
        for (int u = 0; u < 8; u++) bad |= bad4(v[u], tag);
        if (!(bad & 1)) break;
        if (++it > SPIN_LIMIT) __trap();
      }
      __syncwarp();
      float a0 = 0.f, a1 = 0.f, a2 = 0.f, a3 = 0.f;
#pragma unroll
      for (int u = 0; u < 8; u++) {
        a0 += u2f(v[u].x);
        a1 += u2f(v[u].y);
        a2 += u2f(v[u].z);
        a3 += u2f(v[u].w);
      }
      a0 = rbf(bf_lo(bs.x) + rbf(a0));
      a1 = rbf(bf_hi(bs.x) + rbf(a1));
      a2 = rbf(bf_lo(bs.y) + rbf(a2));
      a3 = rbf(bf_hi(bs.y) + rbf(a3));
      *(uint2*)((n ? xpost : xmid) + 4 * quad) = make_uint2(pack_bf16(a0, a1), pack_bf16(a2, a3));
      float mean = 0.25f * ((a0 + a1) + (a2 + a3));
      float m2 = (a0 - mean) * (a0 - mean) + (a1 - mean) * (a1 - mean) + (a2 - mean) * (a2 - mean) + (a3 - mean) * (a3 - mean);
      warp_stats(mean, m2, 4.f);
      if (lane == 0) *(float2*)&stat[w * 2] = make_float2(mean, m2);
      bar_sync(1, 256);
      const int nn = g8 & 1;
      float4 sa = *(const float4*)&stat[nn * 8], sb = *(const float4*)&stat[nn * 8 + 4];
      float ma = 0.5f * (sa.x + sa.z), qa = sa.y + sa.w + (sa.z - sa.x) * (sa.z - sa.x) * 64.f;
      float mc = 0.5f * (sb.x + sb.z), qc = sb.y + sb.w + (sb.z - sb.x) * (sb.z - sb.x) * 64.f;
      float mt_ = 0.5f * (ma + mc), qt = qa + qc + (mc - ma) * (mc - ma) * 128.f;
      float mb, den;
      ln_consts(mt_, qt, mb, den);
      const __nv_bfloat16* xv = (nn ? xpost : xmid) + 64 * w + 4 * j;
      float acc[4] = {0.f, 0.f, 0.f, 0.f};
#pragma unroll
      for (int ks = 0; ks < 4; ks++) {
        uint2 t = *(const uint2*)(xv + 16 * ks);
        uint32_t b0 = pack_bf16(ln_apply(bf_lo(t.x), mb, den), ln_apply(bf_hi(t.x), mb, den));
        uint32_t b1 = pack_bf16(ln_apply(bf_lo(t.y), mb, den), ln_apply(bf_hi(t.y), mb, den));
        mma16816(acc, f1[ks][0], f1[ks][1], f1[ks][2], f1[ks][3], b0, b1);
      }
      if (j == 0) {
        *(float2*)&red1[w * 32 + 2 * g8] = make_float2(acc[0], acc[2]);
        *(float2*)&red1[w * 32 + 16 + 2 * g8] = make_float2(acc[1], acc[3]);
      }
      bar_sync(1, 256);
      if (tid < 32 && cta < 112) {
        float sum = 0.f;
#pragma unroll
        for (int u = 0; u < 8; u++) sum += red1[u * 32 + tid];
        float hv = rbf(sum);
        float sv = rbf(__fdividef(hv, 1.f + __expf(-hv)));
        st_rlx1(&g_h[c][tid >> 4][16 * cta + (tid & 15)], sv, tag);
      }
    }
    {
      float acc[4] = {0.f, 0.f, 0.f, 0.f};
      if (w < 7) {
        const float* hp = &g_h[c][g8 & 1][448 * kq + 64 * w + 4 * j];
        uint4 v[4];
        if (g8 < 2) {
          uint32_t it = 0;
          while (true) {
#pragma unroll
            for (int u = 0; u < 4; u++) v[u] = ld_rlx4(hp + 16 * u);
            uint32_t bad = bad4(v[0], tag) | bad4(v[1], tag) | bad4(v[2], tag) | bad4(v[3], tag);
            if (!(bad & 1)) break;
            if (++it > SPIN_LIMIT) __trap();
          }
        } else {
#pragma unroll
          for (int u = 0; u < 4; u++) v[u] = make_uint4(0u, 0u, 0u, 0u);
        }
        __syncwarp();
#pragma unroll
        for (int ks = 0; ks < 4; ks++) {
          uint32_t b0 = __byte_perm(v[ks].x, v[ks].y, 0x7632), b1 = __byte_perm(v[ks].z, v[ks].w, 0x7632);
          mma16816(acc, f2[ks][0], f2[ks][1], f2[ks][2], f2[ks][3], b0, b1);
        }
      }
      if (j == 0) {
        *(float2*)&red0[w * 32 + 2 * g8] = make_float2(acc[0], acc[2]);
        *(float2*)&red0[w * 32 + 16 + 2 * g8] = make_float2(acc[1], acc[3]);
      }
      bar_sync(1, 256);
      if (tid < 32) {
        float sum = 0.f;
#pragma unroll
        for (int u = 0; u < 7; u++) sum += red0[u * 32 + tid];
        st_rlx1(&g_z[c][tid >> 4][kq][16 * cg + (tid & 15)], sum, tag);
      }
      if (tid == 32 && has_mid) mbar_arrive(bars + 8 * (BAR_LGO + c));
    }
    {
      const bool active = n == 0 ? has_mid : (has_post && quad == cta);
      float a0 = 0.f, a1 = 0.f, a2 = 0.f, a3 = 0.f;
      if (active) {
        const float* zp = &g_z[c][n][0][4 * quad];
        uint4 v[4];
        uint32_t it = 0;
        while (true) {
#pragma unroll
          for (int u = 0; u < 4; u++) v[u] = ld_rlx4(zp + u * 512);
          uint32_t bad = bad4(v[0], tag) | bad4(v[1], tag) | bad4(v[2], tag) | bad4(v[3], tag);
          if (!(bad & 1)) break;
          if (++it > SPIN_LIMIT) __trap();
        }
        uint2 bs = *(const uint2*)((n ? xpost : xmid) + 4 * quad);
        a0 = (u2f(v[0].x) + u2f(v[1].x)) + (u2f(v[2].x) + u2f(v[3].x));
        a1 = (u2f(v[0].y) + u2f(v[1].y)) + (u2f(v[2].y) + u2f(v[3].y));
        a2 = (u2f(v[0].z) + u2f(v[1].z)) + (u2f(v[2].z) + u2f(v[3].z));
        a3 = (u2f(v[0].w) + u2f(v[1].w)) + (u2f(v[2].w) + u2f(v[3].w));
        a0 = rbf(bf_lo(bs.x) + rbf(a0));
        a1 = rbf(bf_hi(bs.x) + rbf(a1));
        a2 = rbf(bf_lo(bs.y) + rbf(a2));
        a3 = rbf(bf_hi(bs.y) + rbf(a3));
        uint2 o = make_uint2(pack_bf16(a0, a1), pack_bf16(a2, a3));
        if (n == 0)
          *(uint2*)(xmid + 4 * quad) = o;
        else
          *(uint2*)(out + (c - 1) * 512 + 4 * quad) = o;
      }
      __syncwarp();
      if (!has_mid) break;
      if (n == 0) {
        float mean = 0.25f * ((a0 + a1) + (a2 + a3));
        float m2 = (a0 - mean) * (a0 - mean) + (a1 - mean) * (a1 - mean) + (a2 - mean) * (a2 - mean) + (a3 - mean) * (a3 - mean);
        warp_stats(mean, m2, 4.f);
        if (lane == 0) *(float2*)&stat[w * 2] = make_float2(mean, m2);
      }
      bar_sync(1, 256);
      float4 sa = *(const float4*)&stat[0], sb = *(const float4*)&stat[4];
      float ma = 0.5f * (sa.x + sa.z), qa = sa.y + sa.w + (sa.z - sa.x) * (sa.z - sa.x) * 64.f;
      float mc = 0.5f * (sb.x + sb.z), qc = sb.y + sb.w + (sb.z - sb.x) * (sb.z - sb.x) * 64.f;
      float mt_ = 0.5f * (ma + mc), qt = qa + qc + (mc - ma) * (mc - ma) * 128.f;
      float mb, den;
      ln_consts(mt_, qt, mb, den);
      const __nv_bfloat16* xv = xmid + 64 * w + 4 * j;
      float acc[2][4] = {{0.f, 0.f, 0.f, 0.f}, {0.f, 0.f, 0.f, 0.f}};
#pragma unroll
      for (int ks = 0; ks < 4; ks++) {
        uint2 t = *(const uint2*)(xv + 16 * ks);
        uint32_t b0 = pack_bf16(ln_apply(bf_lo(t.x), mb, den), ln_apply(bf_hi(t.x), mb, den));
        uint32_t b1 = pack_bf16(ln_apply(bf_lo(t.y), mb, den), ln_apply(bf_hi(t.y), mb, den));
        mma16816(acc[0], fq[ks][0][0], fq[ks][0][1], fq[ks][0][2], fq[ks][0][3], b0, b1);
        mma16816(acc[1], fq[ks][1][0], fq[ks][1][1], fq[ks][1][2], fq[ks][1][3], b0, b1);
      }
      if (j == 0) *(float4*)&red1[w * 32 + 4 * g8] = make_float4(acc[0][0], acc[0][2], acc[1][0], acc[1][2]);
      bar_sync(1, 256);
      if (tid < 32) {
        float sum = 0.f;
#pragma unroll
        for (int u = 0; u < 8; u++) sum += red1[u * 32 + tid];
        st_rlx1(&g_q[1][c][g][q_pos(32 * s + tid)], rbf(sum), tag);
        __syncwarp();
        if (tid == 0) mbar_arrive(bars + 8 * (BAR_QGO + c));
      }
    }
  }
}

__device__ __forceinline__ void producer_role(char* smem, int cta, const CUtensorMap* tmK, const CUtensorMap* tmV,
                                              const char* Kp, const char* Vp) {
  const uint32_t sbase = smem_u32(smem);
  const uint32_t bars = sbase + OFF_BAR;
  const uint32_t freeaddr = sbase + OFF_MISC;
  volatile uint8_t* info = (volatile uint8_t*)(smem + OFF_INFO);
  volatile uint8_t* linfo = info + NB * NT;
  const int g = cta >> 4, s = cta & 15;
  uint64_t pol;
  asm volatile("createpolicy.fractional.L2::evict_first.b64 %0, 1.0;" : "=l"(pol));
  uint32_t freem = (1u << NSLOT) - 1, retm = 0;
  int dn = 0, lb = 0;
  uint32_t trans_cur = 0;
  uint64_t trans_lo = 0, trans_hi = 0;
  uint32_t lpend = 0;
  bool lallowed = false, turnL = false;
  uint32_t it = 0;
  while (dn < NB * NT || lb < NB) {
    if (freem == 0 || (it & 3) == 0) {
      uint32_t nf = grab_free(freeaddr);
      freem |= nf;
      retm &= ~nf;
    }
    if (lb < NB && !lallowed && dn >= (lb + 1) * NT) {
      if (dn >= NB * NT || mbar_test(bars + 8 * (BAR_LGO + lb), 0)) {
        lallowed = true;
        lpend = (uint32_t)(((lb < 4 ? trans_lo : trans_hi) >> (16 * (lb & 3))) & 0xffffu);
      }
    }
    if (lallowed && lpend == 0) {
      lallowed = false;
      lb++;
      continue;
    }
    if (freem) {
      bool doL = lallowed && (turnL || dn >= NB * NT);
      int slot = __ffs(freem) - 1;
      uint32_t dst = sbase + slot * TILE_BYTES;
      if (doL) {
        int t = __ffs(lpend) - 1;
        lpend &= lpend - 1;
        freem &= freem - 1;
        linfo[lb * NT + t] = slot;
        uint32_t fb = bars + 8 * (BAR_FULLL + (lb & 1) * NT + t);
        int row = (lb * 8 + g) * 8192 + s * 512 + t * TK;
        mbar_expect_tx(fb, TILE_BYTES);
        tma3d(dst, tmK, row, fb, pol);
        tma3d(dst + HALF_BYTES, tmV, row, fb, pol);
        turnL = false;
      } else if (dn < NB * NT) {
        int b = dn >> 4, t = dn & 15;
        bool ret = __popc(retm) < RMAX;
        freem &= freem - 1;
        if (ret)
          retm |= 1u << slot;
        else
          trans_cur |= 1u << t;
        info[dn] = slot | (ret ? 0x80 : 0);
        uint32_t fb = bars + 8 * (BAR_FULLD + (b & 1) * NT + t);
        int row = (b * 8 + g) * 8192 + s * 512 + t * TK;
        mbar_expect_tx(fb, TILE_BYTES);
        tma3d(dst, tmK, row, fb, pol);
        tma3d(dst + HALF_BYTES, tmV, row, fb, pol);
        if (!ret) {
          l2_prefetch(Kp + (size_t)row * 256, HALF_BYTES);
          l2_prefetch(Vp + (size_t)row * 256, HALF_BYTES);
        }
        if (t == NT - 1) {
          if (b < 4)
            trans_lo |= (uint64_t)trans_cur << (16 * b);
          else
            trans_hi |= (uint64_t)trans_cur << (16 * (b - 4));
          trans_cur = 0;
        }
        dn++;
        turnL = true;
      }
    }
    if (++it > (SPIN_LIMIT << 2)) __trap();
  }
}

__global__ void __launch_bounds__(NTHREADS, 1)
    fused_kernel(const __grid_constant__ CUtensorMap tmK, const __grid_constant__ CUtensorMap tmV,
                 const __nv_bfloat16* __restrict__ x, const __nv_bfloat16* __restrict__ kc,
                 const __nv_bfloat16* __restrict__ vc, const __nv_bfloat16* __restrict__ wq,
                 const __nv_bfloat16* __restrict__ wo, const __nv_bfloat16* __restrict__ w1,
                 const __nv_bfloat16* __restrict__ w2, __nv_bfloat16* __restrict__ out) {
  extern __shared__ __align__(1024) char smem[];
  const int tid = threadIdx.x, warp = tid >> 5, lane = tid & 31, cta = blockIdx.x;
  if (tid == 0) {
    const uint32_t sbase = smem_u32(smem);
    if (sbase & 1023) __trap();
    const uint32_t bars = sbase + OFF_BAR;
    for (int i = 0; i < 64; i++) mbar_init(bars + 8 * i, 1);
    for (int i = 0; i < 8; i++) {
      mbar_init(bars + 8 * (BAR_P1DONE + i), NW1);
      mbar_init(bars + 8 * (BAR_P2DONE + i), NW2);
      mbar_init(bars + 8 * (BAR_QGO + i), 1);
      mbar_init(bars + 8 * (BAR_LGO + i), 1);
    }
    uint32_t* misc = (uint32_t*)(smem + OFF_MISC);
    misc[0] = 0;
    misc[1] = *(volatile unsigned*)&g_epoch;
    asm volatile("fence.mbarrier_init.release.cluster;" ::: "memory");
  }
  __syncthreads();
  const unsigned epoch = ((const uint32_t*)(smem + OFF_MISC))[1];
  const uint32_t tag = (epoch + 1) & 1;
  if (warp < 8) {
    asm volatile("setmaxnreg.inc.sync.aligned.u32 160;");
    chain_role(smem, tid, cta, tag, x, wq, wo, w1, w2, out);
    if (cta == 0 && tid == 0) *(volatile unsigned*)&g_epoch = epoch + 1;
  } else if (warp < 12) {
    asm volatile("setmaxnreg.dec.sync.aligned.u32 96;");
    if (warp < 8 + NW1) {
      attn_role<0, NW1>(smem, warp - 8, lane, cta, tag);
    } else if (warp == 10 && lane == 0) {
      producer_role(smem, cta, &tmK, &tmV, (const char*)kc, (const char*)vc);
    }
  } else {
    asm volatile("setmaxnreg.dec.sync.aligned.u32 96;");
    attn_role<1, NW2>(smem, warp - 12, lane, cta, tag);
  }
}

typedef CUresult (*EncodeFn)(CUtensorMap*, CUtensorMapDataType, cuuint32_t, void*, const cuuint64_t*, const cuuint64_t*,
                             const cuuint32_t*, const cuuint32_t*, CUtensorMapInterleave, CUtensorMapSwizzle,
                             CUtensorMapL2promotion, CUtensorMapFloatOOBfill);

}

extern "C" void kernel_launch(void* const* d_in, const int* in_sizes, int n_in, void* d_out, int out_size) {
  static EncodeFn enc = nullptr;
  if (!enc) {
    void* fn = nullptr;
    cudaDriverEntryPointQueryResult qr;
    cudaGetDriverEntryPoint("cuTensorMapEncodeTiled", &fn, cudaEnableDefault, &qr);
    enc = (EncodeFn)fn;
    cudaFuncSetAttribute(fused_kernel, cudaFuncAttributeMaxDynamicSharedMemorySize, SMEM_BYTES);
  }
  const __nv_bfloat16* x = (const __nv_bfloat16*)d_in[0];
  const __nv_bfloat16* kc = (const __nv_bfloat16*)d_in[1];
  const __nv_bfloat16* vc = (const __nv_bfloat16*)d_in[2];
  const __nv_bfloat16* wq = (const __nv_bfloat16*)d_in[3];
  const __nv_bfloat16* wo = (const __nv_bfloat16*)d_in[4];
  const __nv_bfloat16* w1 = (const __nv_bfloat16*)d_in[6];
  const __nv_bfloat16* w2 = (const __nv_bfloat16*)d_in[7];
  CUtensorMap tmK, tmV;
  cuuint64_t dims[3] = {64, (cuuint64_t)8 * 8 * 8192, 2};
  cuuint64_t strides[2] = {256, 128};
  cuuint32_t box[3] = {64, TK, 2};
  cuuint32_t es[3] = {1, 1, 1};
  enc(&tmK, CU_TENSOR_MAP_DATA_TYPE_BFLOAT16, 3, (void*)kc, dims, strides, box, es, CU_TENSOR_MAP_INTERLEAVE_NONE,
      CU_TENSOR_MAP_SWIZZLE_128B, CU_TENSOR_MAP_L2_PROMOTION_NONE, CU_TENSOR_MAP_FLOAT_OOB_FILL_NONE);
  enc(&tmV, CU_TENSOR_MAP_DATA_TYPE_BFLOAT16, 3, (void*)vc, dims, strides, box, es, CU_TENSOR_MAP_INTERLEAVE_NONE,
      CU_TENSOR_MAP_SWIZZLE_128B, CU_TENSOR_MAP_L2_PROMOTION_NONE, CU_TENSOR_MAP_FLOAT_OOB_FILL_NONE);
  fused_kernel<<<128, NTHREADS, SMEM_BYTES>>>(tmK, tmV, x, kc, vc, wq, wo, w1, w2, (__nv_bfloat16*)d_out);
}
```

```cpp
#include <cuda_runtime.h>
#include <cuda.h>
#include <cuda_bf16.h>
#include <stdint.h>

namespace {

constexpr int NB = 8;
constexpr int NT = 16;
constexpr int TK = 32;
constexpr int NSLOT = 13;
#define RMAX_ 9
#define WD_ 4
#define WL_ 4
#define LIM_ 30
constexpr int LIM = LIM_;
#define PS_ 100
constexpr int PS = PS_;
#define L2MAX_ 19
constexpr int L2MAX = L2MAX_;
#define RL_ 0
constexpr int RL = RL_;
#define PAUSE_END 0
#define PACE_ 0
constexpr int PACE = PACE_;
#define PACEL_ 0
constexpr int PACEL = PACEL_;
#define SPN_ 40
constexpr int SPN = SPN_;
#define PA 0
#define UB 0
#define BDELAY 300
#define CDELAY 500
#define DDELAY 300
#define RB_ 9
constexpr int RB = RB_;
constexpr int RMAX = RMAX_;
constexpr int WD = WD_;
constexpr int WL = WL_;
constexpr int HALF_BYTES = TK * 256;
constexpr int TILE_BYTES = 2 * HALF_BYTES;
constexpr int PART_STRIDE = 272;
constexpr int NTHREADS = 512;
constexpr int NW1 = 2;
constexpr int NW2 = 4;
constexpr float SCALE_LOG2 = 0.08838834764831845f * 1.4426950408889634f;
constexpr unsigned SPIN_LIMIT = 1u << 24;

constexpr int OFF_MB1 = NSLOT * TILE_BYTES;
constexpr int OFF_MB2 = OFF_MB1 + 2048;
constexpr int OFF_ML1 = OFF_MB2 + 6144;
constexpr int OFF_ML2 = OFF_ML1 + 128;
constexpr int OFF_CH = OFF_ML2 + 128;
constexpr int OFF_REDA = OFF_CH, OFF_REDC = OFF_CH + 4096;
constexpr int OFF_XS = OFF_CH, OFF_RED1 = OFF_CH + 3072;
constexpr int OFF_STAT = OFF_CH + 5120;
constexpr int OFF_CSUM = OFF_STAT + 128;
constexpr int OFF_CH_END = OFF_CH + 6144;
constexpr int OFF_QS = OFF_CH_END;
constexpr int OFF_BAR = OFF_QS + 2048;
constexpr int OFF_INFO = OFF_BAR + 1344;
constexpr int OFF_MISC = OFF_INFO + 256;
constexpr int SMEM_BYTES = OFF_MISC + 32;
#define ST(i)
#define SP(row, i)
constexpr int BAR_FULLD = 0, BAR_FULLL = 64, BAR_P1DONE = 128, BAR_P2DONE = 136, BAR_QGO = 144, BAR_LGO = 152,
              BAR_Q1 = 160;
constexpr uint32_t ST_RET = 1u << 13, ST_L2 = 1u << 18, ST_LOPEN = 1u << 23, ST_DONE = 1u << 24;

__device__ __align__(16) float g_part[2][NB][128][PART_STRIDE];
__device__ __align__(16) float g_y[NB + 1][2][8][256];
__device__ __align__(16) float g_h[NB + 1][2][1792];
__device__ __align__(16) float g_z[NB + 1][2][4][512];
__device__ __align__(16) float g_q[2][NB][8][512];
__device__ unsigned g_epoch;
#define TL(role, idx)
#define TLX(role, idx)

__device__ __forceinline__ uint32_t smem_u32(const void* p) { return (uint32_t)__cvta_generic_to_shared(p); }
__device__ __forceinline__ void mbar_init(uint32_t bar, uint32_t cnt) {
  asm volatile("mbarrier.init.shared::cta.b64 [%0], %1;" ::"r"(bar), "r"(cnt));
}
__device__ __forceinline__ void mbar_arrive(uint32_t bar) {
  asm volatile("mbarrier.arrive.shared::cta.b64 _, [%0];" ::"r"(bar) : "memory");
}
__device__ __forceinline__ void mbar_arrive_relaxed(uint32_t bar) {
  asm volatile("mbarrier.arrive.relaxed.cta.shared::cta.b64 _, [%0];" ::"r"(bar) : "memory");
}
__device__ __forceinline__ void mbar_expect_tx(uint32_t bar, uint32_t bytes) {
  asm volatile("mbarrier.arrive.expect_tx.shared::cta.b64 _, [%0], %1;" ::"r"(bar), "r"(bytes) : "memory");
}
__device__ __forceinline__ void mbar_wait(uint32_t bar, uint32_t parity) {
  uint32_t ok, it = 0;
  do {
    asm volatile(
        "{\n.reg .pred p;\nmbarrier.try_wait.parity.shared::cta.b64 p, [%1], %2;\nselp.u32 %0, 1, 0, p;\n}"
        : "=r"(ok)
        : "r"(bar), "r"(parity)
        : "memory");
    if (++it > SPIN_LIMIT) __trap();
  } while (!ok);
}
__device__ __forceinline__ bool mbar_test(uint32_t bar, uint32_t parity) {
  uint32_t ok;
  asm volatile(
      "{\n.reg .pred p;\nmbarrier.test_wait.parity.shared::cta.b64 p, [%1], %2;\nselp.u32 %0, 1, 0, p;\n}"
      : "=r"(ok)
      : "r"(bar), "r"(parity)
      : "memory");
  return ok;
}
__device__ __forceinline__ void tma_half(uint32_t dst, const CUtensorMap* tm, int row, int part, uint32_t bar,
                                         uint64_t pol) {
  asm volatile(
      "cp.async.bulk.tensor.4d.shared::cluster.global.mbarrier::complete_tx::bytes.L2::cache_hint "
      "[%0], [%1, {%3, %4, %3, %6}], [%2], %5;" ::"r"(dst),
      "l"((uint64_t)tm), "r"(bar), "r"(0), "r"(row), "l"(pol), "r"(part)
      : "memory");
}
__device__ __forceinline__ void tma_prefetch(const CUtensorMap* tm, int row, int part) {
  asm volatile("cp.async.bulk.prefetch.tensor.4d.L2.global [%0, {%1, %2, %1, %3}];" ::"l"((uint64_t)tm), "r"(0), "r"(row),
               "r"(part)
               : "memory");
}
__device__ __forceinline__ void state_add(uint32_t addr, uint32_t v) {
  asm volatile("red.relaxed.cta.shared::cta.add.u32 [%0], %1;" ::"r"(addr), "r"(v) : "memory");
}
__device__ __forceinline__ uint32_t lds32(uint32_t addr) {
  uint32_t v;
  asm volatile("ld.volatile.shared::cta.u32 %0, [%1];" : "=r"(v) : "r"(addr) : "memory");
  return v;
}
__device__ __forceinline__ void sts32(uint32_t addr, uint32_t v) {
  asm volatile("st.volatile.shared::cta.u32 [%0], %1;" ::"r"(addr), "r"(v) : "memory");
}
__device__ __forceinline__ void pause_wait(uint32_t addr) {
  if (PAUSE_END) {
    uint32_t it = 0;
    while (lds32(addr))
      if (++it > (SPIN_LIMIT << 2)) __trap();
  }
}
__device__ __forceinline__ uint32_t lds8(uint32_t addr) {
  uint32_t v;
  asm volatile("ld.volatile.shared::cta.u8 %0, [%1];" : "=r"(v) : "r"(addr) : "memory");
  return v;
}
__device__ __forceinline__ void sts8(uint32_t addr, uint32_t v) {
  asm volatile("st.volatile.shared::cta.u8 [%0], %1;" ::"r"(addr), "r"(v) : "memory");
}
__device__ __forceinline__ void bar_sync(int id, int n) { asm volatile("bar.sync %0, %1;" ::"r"(id), "r"(n) : "memory"); }
__device__ __forceinline__ void mma16816(float (&d)[4], uint32_t a0, uint32_t a1, uint32_t a2, uint32_t a3, uint32_t b0,
                                         uint32_t b1) {
  asm("mma.sync.aligned.m16n8k16.row.col.f32.bf16.bf16.f32 {%0,%1,%2,%3}, {%4,%5,%6,%7}, {%8,%9}, {%0,%1,%2,%3};"
      : "+f"(d[0]), "+f"(d[1]), "+f"(d[2]), "+f"(d[3])
      : "r"(a0), "r"(a1), "r"(a2), "r"(a3), "r"(b0), "r"(b1));
}
__device__ __forceinline__ void ldsm4(uint32_t (&r)[4], uint32_t addr) {
  asm volatile("ldmatrix.sync.aligned.m8n8.x4.shared.b16 {%0,%1,%2,%3}, [%4];"
               : "=r"(r[0]), "=r"(r[1]), "=r"(r[2]), "=r"(r[3])
               : "r"(addr)
               : "memory");
}
__device__ __forceinline__ void ldsm4t(uint32_t (&r)[4], uint32_t addr) {
  asm volatile("ldmatrix.sync.aligned.m8n8.x4.trans.shared.b16 {%0,%1,%2,%3}, [%4];"
               : "=r"(r[0]), "=r"(r[1]), "=r"(r[2]), "=r"(r[3])
               : "r"(addr)
               : "memory");
}
__device__ __forceinline__ uint32_t movm(uint32_t a) {
  uint32_t d;
  asm volatile("movmatrix.sync.aligned.m8n8.trans.b16 %0, %1;" : "=r"(d) : "r"(a));
  return d;
}
__device__ __forceinline__ uint32_t pack_bf16(float lo, float hi) {
  uint32_t d;
  asm("cvt.rn.bf16x2.f32 %0, %1, %2;" : "=r"(d) : "f"(hi), "f"(lo));
  return d;
}
__device__ __forceinline__ float rbf(float x) { return __bfloat162float(__float2bfloat16_rn(x)); }
__device__ __forceinline__ float bf_lo(uint32_t v) { return __uint_as_float(v << 16); }
__device__ __forceinline__ float bf_hi(uint32_t v) { return __uint_as_float(v & 0xffff0000u); }
__device__ __forceinline__ float ex2(float x) {
  float y;
  asm("ex2.approx.ftz.f32 %0, %1;" : "=f"(y) : "f"(x));
  return y;
}
__device__ __forceinline__ uint4 ld_rlx4(const float* p) {
  uint4 v;
  asm volatile(
      "{\n.reg .b64 a, b;\nld.relaxed.gpu.global.v2.b64 {a, b}, [%4];\nmov.b64 {%0,%1}, a;\nmov.b64 {%2,%3}, b;\n}"
      : "=r"(v.x), "=r"(v.y), "=r"(v.z), "=r"(v.w)
      : "l"(p)
      : "memory");
  return v;
}
__device__ __forceinline__ uint32_t tagw(float f, uint32_t tag) { return (__float_as_uint(f) & ~1u) | tag; }
__device__ __forceinline__ void st_rlx4(float* p, float a, float b, float c, float d, uint32_t tag) {
  asm volatile(
      "{\n.reg .b64 a, b;\nmov.b64 a, {%1,%2};\nmov.b64 b, {%3,%4};\nst.relaxed.gpu.global.v2.b64 [%0], {a, b};\n}" ::"l"(p),
      "r"(tagw(a, tag)), "r"(__float_as_uint(b)), "r"(tagw(c, tag)), "r"(__float_as_uint(d))
      : "memory");
}
__device__ __forceinline__ void st_rlx_bf4(float* p, float a, float b, float c, float d, uint32_t tag) {
  uint32_t lo = (pack_bf16(a, b) & ~1u) | tag, hi = pack_bf16(c, d);
  asm volatile("{\n.reg .b64 a;\nmov.b64 a, {%1,%2};\nst.relaxed.gpu.global.b64 [%0], a;\n}" ::"l"(p), "r"(lo), "r"(hi)
               : "memory");
}
__device__ __forceinline__ uint32_t bad4(const uint4& v, uint32_t tag) { return (v.x ^ tag) | (v.z ^ tag); }
template <int N, int SLEEP>
__device__ __forceinline__ void poll(uint4 (&v)[N], const float* p, int stride, uint32_t tag) {
#pragma unroll
  for (int i = 0; i < N; i++) v[i] = ld_rlx4(p + i * stride);
  uint32_t it = 0;
  while (true) {
    uint32_t bad = 0;
#pragma unroll
    for (int i = 0; i < N; i++) bad |= bad4(v[i], tag);
    if (!(bad & 1)) break;
    if (SLEEP) __nanosleep(SLEEP);
#pragma unroll
    for (int i = 0; i < N; i++)
      if (bad4(v[i], tag) & 1) v[i] = ld_rlx4(p + i * stride);
    if (++it > SPIN_LIMIT) __trap();
  }
}
__device__ __forceinline__ uint2 ld_rlx2(const float* p);
__device__ __forceinline__ void ldp(uint4& v, const float* p) { v = ld_rlx4(p); }
__device__ __forceinline__ void ldp(uint2& v, const float* p) { v = ld_rlx2(p); }
__device__ __forceinline__ uint32_t badp(const uint4& v, uint32_t tag) { return bad4(v, tag); }
__device__ __forceinline__ uint32_t badp(const uint2& v, uint32_t tag) { return v.x ^ tag; }
template <int N, typename T>
__device__ __forceinline__ void poll1(T (&v)[N], const float* p, int stride, uint32_t tag) {
#pragma unroll
  for (int i = 0; i < N; i++) ldp(v[i], p + i * stride);
  uint32_t it = 0;
  while (true) {
    uint32_t bad = 0;
#pragma unroll
    for (int i = 0; i < N; i++) bad |= badp(v[i], tag);
    if (!(bad & 1)) break;
#pragma unroll
    for (int i = 0; i < N; i++)
      if (badp(v[i], tag) & 1) ldp(v[i], p + i * stride);
    if (++it > SPIN_LIMIT) __trap();
  }
}
template <int N, int SLEEP, typename T>
__device__ __forceinline__ void pollS(T (&v)[N], const float* p, int stride, uint32_t tag) {
#pragma unroll
  for (int i = 0; i < N; i++) ldp(v[i], p + i * stride);
  uint32_t it = 0;
  while (true) {
    uint32_t bad = 0;
#pragma unroll
    for (int i = 0; i < N; i++) bad |= badp(v[i], tag);
    if (!(bad & 1)) break;
    if (SLEEP) __nanosleep(SLEEP);
#pragma unroll
    for (int i = 0; i < N; i++)
      if (badp(v[i], tag) & 1) ldp(v[i], p + i * stride);
    if (++it > SPIN_LIMIT) __trap();
  }
}
__device__ __forceinline__ float rcp_fast(float x) {
  float y;
  asm("rcp.approx.ftz.f32 %0, %1;" : "=f"(y) : "f"(x));
  return y;
}
__device__ __forceinline__ float u2f(uint32_t u) { return __uint_as_float(u); }
__device__ __forceinline__ int opq(int v) {
  asm volatile("" : "+r"(v));
  return v;
}
__device__ __forceinline__ uint2 ld_rlx2(const float* p) {
  uint2 v;
  asm volatile("{\n.reg .b64 a;\nld.relaxed.gpu.global.b64 a, [%2];\nmov.b64 {%0,%1}, a;\n}"
               : "=r"(v.x), "=r"(v.y)
               : "l"(p)
               : "memory");
  return v;
}
__device__ __forceinline__ void sel_if(float& o, float v, int a, int b) {
  asm("{\n.reg .pred p;\nsetp.eq.s32 p, %2, %3;\nselp.f32 %0, %1, %0, p;\n}" : "+f"(o) : "f"(v), "r"(a), "r"(b));
}

__device__ __forceinline__ void ln_consts(float sx, float sxx, float& mb, float& rden) {
  float mean = sx * (1.f / 512.f);
  float var = fmaxf(fmaf(-mean, mean, sxx * (1.f / 512.f)), 0.f);
  mb = rbf(mean);
  float sq;
  asm("sqrt.approx.ftz.f32 %0, %1;" : "=f"(sq) : "f"(rbf(rbf(var) + 1e-5f)));
  rden = rcp_fast(rbf(sq));
}

struct AttnState {
  float acc[8][4];
  float m0, m1, l0, l1;
};

__device__ __forceinline__ void process_tile(uint32_t slot_addr, uint32_t kb, uint32_t vb, const uint32_t (&qf)[8][2],
                                             AttnState& st) {
  auto kaddr = [&](int i) { return slot_addr + (kb ^ (((i >> 1) & 3) << 5)) + (i >> 3) * 4096 + (i & 1) * 2048; };
  auto vaddr = [&](int i) { return slot_addr + (vb ^ ((i & 3) << 5)) + ((i >> 2) & 1) * 4096 + (i >> 3) * 2048; };
  uint32_t a[4][4];
  float sv[2][4];
#pragma unroll
  for (int kg = 0; kg < 2; kg++)
#pragma unroll
    for (int i = 0; i < 4; i++) sv[kg][i] = 0.f;
#pragma unroll
  for (int i = 0; i < 4; i++) ldsm4(a[i], kaddr(i));
#pragma unroll
  for (int i = 0; i < 16; i++) {
    mma16816(sv[i & 1], a[i & 3][0], a[i & 3][1], a[i & 3][2], a[i & 3][3], qf[i >> 1][0], qf[i >> 1][1]);
    if (i + 4 < 16) ldsm4(a[i & 3], kaddr(i + 4));
  }
#pragma unroll
  for (int i = 0; i < 4; i++) ldsm4t(a[i], vaddr(i));
  float t0 = fmaxf(fmaxf(sv[0][0], sv[0][2]), fmaxf(sv[1][0], sv[1][2]));
  float t1 = fmaxf(fmaxf(sv[0][1], sv[0][3]), fmaxf(sv[1][1], sv[1][3]));
#pragma unroll
  for (int o = 4; o < 32; o <<= 1) {
    t0 = fmaxf(t0, __shfl_xor_sync(0xffffffffu, t0, o));
    t1 = fmaxf(t1, __shfl_xor_sync(0xffffffffu, t1, o));
  }
  if (__any_sync(0xffffffffu, (t0 > st.m0) || (t1 > st.m1))) {
    float n0 = fmaxf(st.m0, t0), n1 = fmaxf(st.m1, t1);
    float a0 = ex2((st.m0 - n0) * SCALE_LOG2), a1 = ex2((st.m1 - n1) * SCALE_LOG2);
    st.m0 = n0;
    st.m1 = n1;
    st.l0 *= a0;
    st.l1 *= a1;
#pragma unroll
    for (int mt = 0; mt < 8; mt++) {
      st.acc[mt][0] *= a0;
      st.acc[mt][1] *= a1;
      st.acc[mt][2] *= a0;
      st.acc[mt][3] *= a1;
    }
  }
  const float c0 = -st.m0 * SCALE_LOG2, c1 = -st.m1 * SCALE_LOG2;
  uint32_t pb[2][2];
#pragma unroll
  for (int kg = 0; kg < 2; kg++) {
    float p0 = ex2(fmaf(sv[kg][0], SCALE_LOG2, c0));
    float p1 = ex2(fmaf(sv[kg][1], SCALE_LOG2, c1));
    float p2 = ex2(fmaf(sv[kg][2], SCALE_LOG2, c0));
    float p3 = ex2(fmaf(sv[kg][3], SCALE_LOG2, c1));
    st.l0 += p0 + p2;
    st.l1 += p1 + p3;
    pb[kg][0] = movm(pack_bf16(p0, p1));
    pb[kg][1] = movm(pack_bf16(p2, p3));
  }
#pragma unroll
  for (int i = 0; i < 16; i++) {
    mma16816(st.acc[i & 7], a[i & 3][0], a[i & 3][1], a[i & 3][2], a[i & 3][3], pb[i >> 3][0], pb[i >> 3][1]);
    if (i + 4 < 16) ldsm4t(a[i & 3], vaddr(i + 4));
  }
}

template <int SLEEP>
__device__ __forceinline__ void fetch_q(uint32_t (&qf)[8][2], const float* q, int lane, uint32_t tag) {
  const float* qp = q + ((lane >> 2) & 3) * 128 + (lane >> 4) * 64 + (lane & 3) * 16;
  uint4 v[4];
  if (SLEEP)
    poll<4, SLEEP>(v, qp, 4, tag);
  else
    poll1<4>(v, qp, 4, tag);
  __syncwarp();
#pragma unroll
  for (int u = 0; u < 4; u++) {
    uint32_t r0 = __byte_perm(v[u].x, v[u].y, 0x7632);
    uint32_t r1 = __byte_perm(v[u].z, v[u].w, 0x7632);
    uint32_t o0 = __shfl_down_sync(0xffffffffu, r0, 16);
    uint32_t o1 = __shfl_down_sync(0xffffffffu, r1, 16);
    bool lo = lane < 16;
    qf[u][0] = lo ? r0 : 0u;
    qf[u][1] = lo ? r1 : 0u;
    qf[4 + u][0] = lo ? o0 : 0u;
    qf[4 + u][1] = lo ? o1 : 0u;
  }
}

template <int LAYER, int NW>
__device__ __forceinline__ void attn_role(char* smem, int w_, int lane_, int cta_, uint32_t ep1, uint32_t koff) {
  const int w = w_, lane = lane_;
  const uint32_t tag = ep1 & 1;
  const uint32_t sbase = smem_u32(smem);
  const uint32_t bars = sbase + OFF_BAR;
  const uint32_t state = sbase + OFF_MISC;
  const uint32_t info = sbase + OFF_INFO, linfo = info + NB * NT;
  float* mbuf = (float*)(smem + (LAYER ? OFF_MB2 : OFF_MB1));
  float* mlbuf = (float*)(smem + (LAYER ? OFF_ML2 : OFF_ML1));
  const uint32_t x7 = lane & 7;
  const uint32_t kb = (x7 + 8 * ((lane >> 3) & 1)) * 128 + ((((uint32_t)lane >> 4) ^ x7) << 4) + koff;
  const uint32_t vb = (x7 + 8 * (lane >> 4)) * 128 + (((((uint32_t)lane >> 3) & 1) ^ x7) << 4) + (koff ^ HALF_BYTES);
  uint32_t lpar = 0;

#pragma unroll 1
  for (int b = 0; b < NB; b++) {
    uint32_t qf[8][2];
    {
      const int lane = opq(lane_), cta = opq(cta_);
      if (LAYER == 1) mbar_wait(bars + 8 * (BAR_QGO + b), 0);
      if (w == 0 && lane == 0) TL(1 + LAYER, b * 8 + 0);
      if (LAYER == 1 || b == 0) {
        fetch_q<LAYER ? 50 : 100>(qf, &g_q[LAYER][b][cta >> 4][0], lane, tag);
        if (lane == 0) mbar_arrive(bars + 8 * (LAYER == 0 ? BAR_Q1 : BAR_LGO + b));
        if (LAYER == 1 && (cta & 1) && w == 0 && lane == 0) sts32(sbase + OFF_MISC + 8, 0u);
      } else {
        const uint4* qs = (const uint4*)(smem + OFF_QS + (b & 1) * 1024 + (lane & 15) * 64);
#pragma unroll
        for (int u = 0; u < 4; u++) {
          uint4 t = lane < 16 ? qs[u] : make_uint4(0u, 0u, 0u, 0u);
          qf[2 * u][0] = t.x;
          qf[2 * u][1] = t.y;
          qf[2 * u + 1][0] = t.z;
          qf[2 * u + 1][1] = t.w;
        }
      }
    }
    if (w == 0 && lane == 0) TL(1 + LAYER, b * 8 + 1);
    AttnState st;
#pragma unroll
    for (int mt = 0; mt < 8; mt++)
#pragma unroll
      for (int i = 0; i < 4; i++) st.acc[mt][i] = 0.f;
    st.m0 = st.m1 = -INFINITY;
    st.l0 = st.l1 = 0.f;

    if (LAYER == 0) {
#pragma unroll 1
      for (int t = w; t < NT; t += NW) {
        const uint32_t fb = bars + 8 * (BAR_FULLD + ((b & 1) * NT + t) * 2);
        mbar_wait(fb, (b >> 1) & 1);
        mbar_wait(fb + 8, (b >> 1) & 1);
        uint32_t inf = lds8(info + b * NT + t);
        uint32_t slot = inf & 0x3f;
        process_tile(sbase + slot * TILE_BYTES, kb, vb, qf, st);
        __syncwarp();
        if (!(inf & 0x80) && lane == 0) state_add(state, 1u << slot);
        if (t == 8 && b + 1 < NB) {
          const int ln = opq(lane_);
          const float* qp = &g_q[0][b + 1][opq(cta_) >> 4][((ln >> 2) & 3) * 128 + (ln >> 4) * 64 + (ln & 3) * 16];
          uint4 v[4];
          poll<4, 100>(v, qp, 4, tag);
          uint4* qs = (uint4*)(smem + OFF_QS + ((b + 1) & 1) * 1024 + (ln & 15) * 64 + (ln >> 4) * 32);
          qs[0] = make_uint4(__byte_perm(v[0].x, v[0].y, 0x7632), __byte_perm(v[0].z, v[0].w, 0x7632),
                             __byte_perm(v[1].x, v[1].y, 0x7632), __byte_perm(v[1].z, v[1].w, 0x7632));
          qs[1] = make_uint4(__byte_perm(v[2].x, v[2].y, 0x7632), __byte_perm(v[2].z, v[2].w, 0x7632),
                             __byte_perm(v[3].x, v[3].y, 0x7632), __byte_perm(v[3].z, v[3].w, 0x7632));
          __syncwarp();
        }
      }
    } else {
#pragma unroll 1
      for (int i = 0; i < 2 * (NT / NW); i++) {
        int t = w + NW * (i % (NT / NW));
        uint32_t inf = lds8(info + b * NT + t);
        bool ret = inf & 0x80;
        if (ret != (i < NT / NW)) continue;
        uint32_t slot = inf & 0x3f;
        if (!ret) {
          int bi = (b & 1) * NT + t;
          mbar_wait(bars + 8 * (BAR_FULLL + 2 * bi), (lpar >> bi) & 1);
          mbar_wait(bars + 8 * (BAR_FULLL + 2 * bi + 1), (lpar >> bi) & 1);
          lpar ^= 1u << bi;
          slot = lds8(linfo + b * NT + t);
        }
        process_tile(sbase + slot * TILE_BYTES, kb, vb, qf, st);
        __syncwarp();
        if (lane == 0) state_add(state, (1u << slot) + ST_DONE - (ret ? ST_RET : 0u));
      }
    }

    if (lane == 0) TL(1 + LAYER, b * 8 + 2 + (w & 1));
    {
    const int lane = opq(lane_), w = opq(w_), cta = opq(cta_), g8 = lane >> 2, j = lane & 3;
    constexpr int OWN = 8 / NW;
#pragma unroll
    for (int o = 4; o < 32; o <<= 1) {
      st.l0 += __shfl_xor_sync(0xffffffffu, st.l0, o);
      st.l1 += __shfl_xor_sync(0xffffffffu, st.l1, o);
    }
    if (lane < 2) *(float4*)&mlbuf[w * 8 + lane * 4] = make_float4(st.m0, st.l0, st.m1, st.l1);
    if (j < 2) {
#pragma unroll
      for (int mt = 0; mt < 8; mt++) {
        int ow = mt / OWN;
        if (ow != w) {
          int sr = (w - ow - 1) & (NW - 1);
          *(float4*)&mbuf[(((ow * (NW - 1) + sr) * OWN + (mt % OWN)) * 16 + g8 * 2 + j) * 4] =
              make_float4(st.acc[mt][0], st.acc[mt][1], st.acc[mt][2], st.acc[mt][3]);
        }
      }
    }
    bar_sync(2 + LAYER, 32 * NW);
    if (j < 2) {
      float4 mlv[NW];
#pragma unroll
      for (int u = 0; u < NW; u++) mlv[u] = *(const float4*)&mlbuf[((w + u) & (NW - 1)) * 8 + j * 4];
      float M0 = mlv[0].x, M1 = mlv[0].z;
#pragma unroll
      for (int u = 1; u < NW; u++) {
        M0 = fmaxf(M0, mlv[u].x);
        M1 = fmaxf(M1, mlv[u].z);
      }
      float f0[NW], f1[NW], L0 = 0.f, L1 = 0.f;
#pragma unroll
      for (int u = 0; u < NW; u++) {
        f0[u] = ex2((mlv[u].x - M0) * SCALE_LOG2);
        f1[u] = ex2((mlv[u].z - M1) * SCALE_LOG2);
        L0 = fmaf(f0[u], mlv[u].y, L0);
        L1 = fmaf(f1[u], mlv[u].w, L1);
      }
      float* pp = &g_part[LAYER][b][cta][0];
#pragma unroll
      for (int e2 = 0; e2 < OWN / 2; e2++) {
        float o[2][4];
#pragma unroll
        for (int e1 = 0; e1 < 2; e1++) {
          const int e = 2 * e2 + e1;
          float o0 = 0.f, o1 = 0.f, o2 = 0.f, o3 = 0.f;
#pragma unroll
          for (int cw = 0; cw < NW; cw++) {
            sel_if(o0, st.acc[OWN * cw + e][0], w, cw);
            sel_if(o1, st.acc[OWN * cw + e][1], w, cw);
            sel_if(o2, st.acc[OWN * cw + e][2], w, cw);
            sel_if(o3, st.acc[OWN * cw + e][3], w, cw);
          }
          o0 *= f0[0];
          o1 *= f1[0];
          o2 *= f0[0];
          o3 *= f1[0];
#pragma unroll
          for (int sr = 0; sr < NW - 1; sr++) {
            float4 a = *(const float4*)&mbuf[(((w * (NW - 1) + sr) * OWN + e) * 16 + g8 * 2 + j) * 4];
            o0 = fmaf(a.x, f0[sr + 1], o0);
            o1 = fmaf(a.y, f1[sr + 1], o1);
            o2 = fmaf(a.z, f0[sr + 1], o2);
            o3 = fmaf(a.w, f1[sr + 1], o3);
          }
          o[e1][0] = o0;
          o[e1][1] = o1;
          o[e1][2] = o2;
          o[e1][3] = o3;
        }
        const int u = (OWN / 2) * w + e2;
        st_rlx_bf4(pp + (2 * j) * 64 + u * 16 + 2 * g8, o[0][0], o[0][2], o[1][0], o[1][2], tag);
        st_rlx_bf4(pp + (2 * j + 1) * 64 + u * 16 + 2 * g8, o[0][1], o[0][3], o[1][1], o[1][3], tag);
      }
      if (w == 0 && g8 == 0) st_rlx4(pp + 256 + 4 * j, M0, L0, M1, L1, tag);
    }
    __syncwarp();
    if (w == 0 && lane == 0) TL(1 + LAYER, b * 8 + 4);
    if (lane == 0) mbar_arrive_relaxed(bars + 8 * ((LAYER ? BAR_P2DONE : BAR_P1DONE) + b));
    bar_sync(2 + LAYER, 32 * NW);
    }
  }
}

constexpr uint32_t ONES2 = 0x3F803F80u;

template <int SLEEP>
__device__ __forceinline__ void attn_out(const float* part  , int g, int w, int lane, uint32_t tag,
                                         const uint32_t (&wa)[4][4][4], float* red) {
  const int g8 = lane >> 2, j = lane & 3;
  const float* base = part + (size_t)(16 * g + g8) * PART_STRIDE;
  const float* po = base + 32 * w + 4 * j;
  const float* pm = base + 256 + 2 * (w >> 1);
  uint2 ml0 = ld_rlx2(pm), ml1 = ld_rlx2(pm + 8 * PART_STRIDE);
  uint4 o4[2][2];
#pragma unroll
  for (int sg = 0; sg < 2; sg++)
#pragma unroll
    for (int u = 0; u < 2; u++) o4[sg][u] = ld_rlx4(po + sg * 8 * PART_STRIDE + 16 * u);
  uint32_t it = 0;
  while (true) {
    const uint32_t bad0 = (ml0.x ^ tag) | bad4(o4[0][0], tag) | bad4(o4[0][1], tag);
    const uint32_t bad1 = (ml1.x ^ tag) | bad4(o4[1][0], tag) | bad4(o4[1][1], tag);
    if (!((bad0 | bad1) & 1)) break;
    if (SLEEP) __nanosleep(SLEEP);
    if (bad0 & 1) {
      ml0 = ld_rlx2(pm);
      o4[0][0] = ld_rlx4(po);
      o4[0][1] = ld_rlx4(po + 16);
    }
    if (bad1 & 1) {
      ml1 = ld_rlx2(pm + 8 * PART_STRIDE);
      o4[1][0] = ld_rlx4(po + 8 * PART_STRIDE);
      o4[1][1] = ld_rlx4(po + 8 * PART_STRIDE + 16);
    }
    if (++it > SPIN_LIMIT) __trap();
  }
  __syncwarp();
  float M = fmaxf(u2f(ml0.x), u2f(ml1.x));
#pragma unroll
  for (int o = 4; o < 32; o <<= 1) M = fmaxf(M, __shfl_xor_sync(0xffffffffu, M, o));
  float fo0 = ex2((u2f(ml0.x) - M) * SCALE_LOG2), fo1 = ex2((u2f(ml1.x) - M) * SCALE_LOG2);
  float L = fmaf(fo0, u2f(ml0.y), fo1 * u2f(ml1.y));
#pragma unroll
  for (int o = 4; o < 32; o <<= 1) L += __shfl_xor_sync(0xffffffffu, L, o);
  const float inv = rcp_fast(L);
  fo0 *= inv;
  fo1 *= inv;
  float y[8];
#pragma unroll
  for (int sg = 0; sg < 2; sg++) {
    float acc[4][4];
#pragma unroll
    for (int mt = 0; mt < 4; mt++)
#pragma unroll
      for (int i = 0; i < 4; i++) acc[mt][i] = 0.f;
#pragma unroll
    for (int ks = 0; ks < 4; ks++) {
      const uint32_t b0 = (ks & 1) ? o4[sg][ks >> 1].z : o4[sg][ks >> 1].x;
      const uint32_t b1 = (ks & 1) ? o4[sg][ks >> 1].w : o4[sg][ks >> 1].y;
#pragma unroll
      for (int mt = 0; mt < 4; mt++) mma16816(acc[mt], wa[ks][mt][0], wa[ks][mt][1], wa[ks][mt][2], wa[ks][mt][3], b0, b1);
    }
    const float f0 = __shfl_sync(0xffffffffu, sg ? fo1 : fo0, 8 * j);
    const float f1 = __shfl_sync(0xffffffffu, sg ? fo1 : fo0, 8 * j + 4);
#pragma unroll
    for (int mt = 0; mt < 4; mt++)
#pragma unroll
      for (int hf = 0; hf < 2; hf++) {
        const float t = fmaf(f0, acc[mt][2 * hf], f1 * acc[mt][2 * hf + 1]);
        y[2 * mt + hf] = sg ? y[2 * mt + hf] + t : t;
      }
  }
#pragma unroll
  for (int o = 1; o < 4; o <<= 1) {
#pragma unroll
    for (int i = 0; i < 8; i++) y[i] += __shfl_xor_sync(0xffffffffu, y[i], o);
  }
  if (j == 0) {
    *(float4*)&red[8 * g8] = make_float4(y[0], y[1], y[2], y[3]);
    *(float4*)&red[8 * g8 + 4] = make_float4(y[4], y[5], y[6], y[7]);
  }
}

__device__ __forceinline__ int q_lpos(int c) {
  int kk = c >> 4, r = c & 15;
  return ((r & 7) >> 1) * 16 + kk * 4 + (r & 1) + 2 * (r >> 3);
}

__device__ __forceinline__ float4 sum8(const float* p, int stride) {
  float4 a = *(const float4*)p;
#pragma unroll
  for (int u = 1; u < 8; u++) {
    float4 t = *(const float4*)(p + u * stride);
    a.x += t.x;
    a.y += t.y;
    a.z += t.z;
    a.w += t.w;
  }
  return a;
}

#define CHAIN_IDS                                                                                             \
  const int tid = opq(tid_), cta = opq(cta_);                                                                 \
  const int w = tid >> 5, lane = tid & 31, g8 = lane >> 2, j = lane & 3;                                      \
  const int g = cta >> 4, hb = (cta & 15) >> 1, i64 = g * 8 + hb, cb = i64 & 15, kq = i64 >> 4;               \
  const int n = tid >> 7, quad = tid & 127;                                                                   \
  const uint32_t ones_row = g8 == 0 ? ONES2 : 0u;                                                             \
  (void)w, (void)lane, (void)g8, (void)j, (void)g, (void)hb, (void)i64, (void)cb, (void)kq, (void)n, (void)quad, \
      (void)ones_row;

template <typename F>
__device__ __forceinline__ void load_wa(uint32_t (&wa)[4][4][4], const __nv_bfloat16* base, int pitch, F rowf) {
#pragma unroll
  for (int ks = 0; ks < 4; ks++) {
    uint4 r[4];
#pragma unroll
    for (int e = 0; e < 4; e++) r[e] = __ldg((const uint4*)(base + (size_t)rowf(ks, e) * pitch));
    const uint32_t c0[4] = {r[0].x, r[0].y, r[0].z, r[0].w}, c1[4] = {r[1].x, r[1].y, r[1].z, r[1].w};
    const uint32_t c2[4] = {r[2].x, r[2].y, r[2].z, r[2].w}, c3[4] = {r[3].x, r[3].y, r[3].z, r[3].w};
#pragma unroll
    for (int mt = 0; mt < 4; mt++) {
      wa[ks][mt][0] = __byte_perm(c0[mt], c1[mt], 0x5410);
      wa[ks][mt][1] = __byte_perm(c0[mt], c1[mt], 0x7632);
      wa[ks][mt][2] = __byte_perm(c2[mt], c3[mt], 0x5410);
      wa[ks][mt][3] = __byte_perm(c2[mt], c3[mt], 0x7632);
    }
  }
}

__device__ __forceinline__ void chain_role(char* smem, int tid_, int cta_, uint32_t ep1, const __nv_bfloat16* __restrict__ x,
                                           const __nv_bfloat16* __restrict__ wq, const __nv_bfloat16* __restrict__ wo,
                                           const __nv_bfloat16* __restrict__ w1, const __nv_bfloat16* __restrict__ w2,
                                           __nv_bfloat16* __restrict__ out) {
  const uint32_t sbase = smem_u32(smem);
  const uint32_t bars = sbase + OFF_BAR;
  const uint32_t pause = sbase + OFF_MISC + 8;
  const uint32_t tag = ep1 & 1;
  const bool set1 = cta_ & 1;
  __nv_bfloat16* xs = (__nv_bfloat16*)(smem + OFF_XS);
  float* redA = (float*)(smem + OFF_REDA);
  float* redC = (float*)(smem + OFF_REDC);
  float* red1 = (float*)(smem + OFF_RED1);
  float* stat = (float*)(smem + OFF_STAT);
  float* csum = (float*)(smem + OFF_CSUM);

  uint32_t wa[4][4][4];
  uint32_t wb[4][2][4];

  if (set1) {
    {
      CHAIN_IDS
      const uint4* xp = (const uint4*)x;
      uint4 x0 = __ldg(xp + tid), x1 = __ldg(xp + tid + 256);
      load_wa(wa, wq + 512 * g + 64 * hb + 8 * g8, 4096, [&](int ks, int e) { return 64 * w + 16 * ks + 4 * j + e; });
      uint4* xn = (uint4*)(smem + OFF_MB1);
      xn[tid] = x0;
      xn[tid + 256] = x1;
    }
    bar_sync(1, 256);
    {
      CHAIN_IDS
      float c[4][4], cs[4][4], sa[4] = {0.f, 0.f, 0.f, 0.f};
#pragma unroll
      for (int mt = 0; mt < 4; mt++)
#pragma unroll
        for (int i = 0; i < 4; i++) c[mt][i] = cs[mt][i] = 0.f;
#pragma unroll
      for (int ks = 0; ks < 4; ks++) {
        uint2 bv = *(const uint2*)(smem + OFF_MB1 + (g8 * 512 + 64 * w + 16 * ks + 4 * j) * 2);
#pragma unroll
        for (int mt = 0; mt < 4; mt++) {
          mma16816(c[mt], wa[ks][mt][0], wa[ks][mt][1], wa[ks][mt][2], wa[ks][mt][3], bv.x, bv.y);
          mma16816(cs[mt], wa[ks][mt][0], wa[ks][mt][1], wa[ks][mt][2], wa[ks][mt][3], ONES2, ONES2);
        }
        mma16816(sa, bv.x, ones_row, bv.y, ones_row, bv.x, bv.y);
      }
      float* st16 = (float*)(smem + OFF_XS);
      if (j == 0) {
#pragma unroll
        for (int mt = 0; mt < 4; mt++)
#pragma unroll
          for (int hf = 0; hf < 2; hf++) red1[w * 64 + q_lpos(8 * g8 + 2 * mt + hf)] = cs[mt][2 * hf];
      }
      if (j == (g8 >> 1)) st16[w * 16 + g8] = (g8 & 1) ? sa[1] : sa[0];
      if (g8 == 0) {
        st16[w * 16 + 8 + 2 * j] = sa[2];
        st16[w * 16 + 8 + 2 * j + 1] = sa[3];
      }
      float* rb = (float*)(smem + OFF_MB1);
#pragma unroll
      for (int rnd = 0; rnd < 2; rnd++) {
        bar_sync(1, 256);
        if ((j >> 1) == rnd) {
#pragma unroll
          for (int mt = 0; mt < 4; mt++)
#pragma unroll
            for (int hf = 0; hf < 2; hf++) {
              const int lp = q_lpos(8 * g8 + 2 * mt + hf);
              rb[(w * 4 + 2 * (j & 1)) * 64 + lp] = c[mt][2 * hf];
              rb[(w * 4 + 2 * (j & 1) + 1) * 64 + lp] = c[mt][2 * hf + 1];
            }
        }
        bar_sync(1, 256);
        if (tid < 64) {
          const int nl = tid >> 4, qd = tid & 15, nb = 4 * rnd + nl;
          float4 a = sum8(rb + nl * 64 + 4 * qd, 256);
          float4 cs4 = sum8(red1 + 4 * qd, 64);
          float sxx = 0.f, sx = 0.f;
#pragma unroll
          for (int u = 0; u < 8; u++) {
            sxx += st16[u * 16 + nb];
            sx += st16[u * 16 + 8 + nb];
          }
          float mb, rden;
          ln_consts(sx, sxx, mb, rden);
          st_rlx4(&g_q[0][nb][g][64 * hb + 4 * qd], rbf((a.x - mb * cs4.x) * rden), rbf((a.y - mb * cs4.y) * rden),
                  rbf((a.z - mb * cs4.z) * rden), rbf((a.w - mb * cs4.w) * rden), tag);
          if (nb == 0) *(float4*)&csum[4 * qd] = cs4;
        }
      }
      if (tid == 0) TL(0, 200);
    }
  }
  mbar_wait(bars + 8 * BAR_Q1, 0);
  {
    CHAIN_IDS
    if (!set1)
      load_wa(wa, wo + (size_t)512 * g * 512 + 64 * hb + 8 * g8, 512, [&](int ks, int e) {
        const int p = 64 * w + 32 * (ks >> 1) + 8 * j + 4 * (ks & 1) + e;
        const int pp = p & 127;
        return (p & ~127) + (pp >> 5) * 32 + ((pp >> 1) & 1) * 16 + ((pp & 31) >> 2) + 8 * (pp & 1);
      });
    const __nv_bfloat16* bp = set1 ? w1 + 32 * i64 + 4 * g8 : w2 + (size_t)448 * kq * 512 + 32 * cb + 4 * g8;
    const int pitch = set1 ? 1792 : 512;
    const bool valid = set1 ? i64 < 56 : w < 7;
    uint2 r[4][4];
#pragma unroll
    for (int ks = 0; ks < 4; ks++)
#pragma unroll
      for (int e = 0; e < 4; e++)
        r[ks][e] = valid ? __ldg((const uint2*)(bp + (size_t)(64 * w + 16 * ks + 4 * j + e) * pitch)) : make_uint2(0u, 0u);
#pragma unroll
    for (int ks = 0; ks < 4; ks++) {
      wb[ks][0][0] = __byte_perm(r[ks][0].x, r[ks][1].x, 0x5410);
      wb[ks][0][1] = __byte_perm(r[ks][0].x, r[ks][1].x, 0x7632);
      wb[ks][0][2] = __byte_perm(r[ks][2].x, r[ks][3].x, 0x5410);
      wb[ks][0][3] = __byte_perm(r[ks][2].x, r[ks][3].x, 0x7632);
      wb[ks][1][0] = __byte_perm(r[ks][0].y, r[ks][1].y, 0x5410);
      wb[ks][1][1] = __byte_perm(r[ks][0].y, r[ks][1].y, 0x7632);
      wb[ks][1][2] = __byte_perm(r[ks][2].y, r[ks][3].y, 0x5410);
      wb[ks][1][3] = __byte_perm(r[ks][2].y, r[ks][3].y, 0x7632);
    }
    bar_sync(1, 256);
    if (set1) {
      float cs[2][4] = {{0.f, 0.f, 0.f, 0.f}, {0.f, 0.f, 0.f, 0.f}};
#pragma unroll
      for (int ks = 0; ks < 4; ks++) {
        mma16816(cs[0], wb[ks][0][0], wb[ks][0][1], wb[ks][0][2], wb[ks][0][3], ONES2, ONES2);
        mma16816(cs[1], wb[ks][1][0], wb[ks][1][1], wb[ks][1][2], wb[ks][1][3], ONES2, ONES2);
      }
      if (j == 0) *(float4*)&red1[w * 32 + 4 * g8] = make_float4(cs[0][0], cs[0][2], cs[1][0], cs[1][2]);
      *(uint2*)(xs + 512 + 4 * tid) = make_uint2(0u, 0u);
    } else {
      if (tid < 128) *(float4*)&redA[(tid >> 4) * 128 + 64 + 4 * (tid & 15)] = make_float4(0.f, 0.f, 0.f, 0.f);
    }
    bar_sync(1, 256);
    if (set1 && tid < 8) *(float4*)&csum[64 + 4 * tid] = sum8(red1 + 4 * tid, 32);
    if (tid == 0) TL(0, 201);
  }

#pragma unroll 1
  for (int c = 0; c <= NB; c++) {
    const bool has_mid = c < NB, has_post = c >= 2;
    if (!set1) {
      {
        CHAIN_IDS
        if (has_post) {
          mbar_wait(bars + 8 * (BAR_P2DONE + c - 2), 0);
          if (tid == 0) TLX(0, c * 16 + 0);
          attn_out<300>(&g_part[1][c - 2][0][0], g, w, lane, tag, wa, redA + w * 128 + (has_mid ? 64 : 0));
          if (tid == 0) TLX(0, c * 16 + 1);
        }
        mbar_wait(bars + 8 * (has_mid ? BAR_P1DONE + c : BAR_P2DONE + NB - 1), 0);
        if (PA && tid == 32) sts32(pause, 1u);
        if (tid == 0) TL(0, c * 16 + 2);
        attn_out<PS>(has_mid ? &g_part[0][c][0][0] : &g_part[1][NB - 1][0][0], g, w, lane, tag, wa,
                     redA + w * 128 + (has_mid ? 0 : 64));
        if (tid == 0) TLX(0, c * 16 + 3);
        bar_sync(1, 256);
        if (tid == 32) sts32(pause, CDELAY ? 0u : 1u);
        if (tid < 32) {
          float4 a = sum8(redA + 4 * tid, 128);
          st_rlx_bf4(&g_y[c][tid >> 4][g][32 * hb + 2 * (tid & 15)], a.x, a.y, a.z, a.w, tag);
        }
        if (tid == 0) TLX(0, c * 16 + 4);
      }
      {
        CHAIN_IDS
        __nanosleep(CDELAY ? CDELAY : 400);
        if (tid == 32) sts32(pause, 1u);
        float acc[2][4] = {{0.f, 0.f, 0.f, 0.f}, {0.f, 0.f, 0.f, 0.f}};
        if (w < 7) {
          const float* hp = &g_h[c][g8 & 1][448 * kq + 64 * w + 4 * j];
          uint4 v[4];
          if (g8 < 2) {
            poll1<4>(v, hp, 16, tag);
          } else {
#pragma unroll
            for (int u = 0; u < 4; u++) v[u] = make_uint4(0u, 0u, 0u, 0u);
          }
          __syncwarp();
          if (tid == 0) TLX(0, c * 16 + 7);
#pragma unroll
          for (int ks = 0; ks < 4; ks++) {
            const uint32_t b0 = __byte_perm(v[ks].x, v[ks].y, 0x7632), b1 = __byte_perm(v[ks].z, v[ks].w, 0x7632);
            mma16816(acc[0], wb[ks][0][0], wb[ks][0][1], wb[ks][0][2], wb[ks][0][3], b0, b1);
            mma16816(acc[1], wb[ks][1][0], wb[ks][1][1], wb[ks][1][2], wb[ks][1][3], b0, b1);
          }
        }
        if (j == 0) {
          *(float4*)&redC[w * 64 + 4 * g8] = make_float4(acc[0][0], acc[0][2], acc[1][0], acc[1][2]);
          *(float4*)&redC[w * 64 + 32 + 4 * g8] = make_float4(acc[0][1], acc[0][3], acc[1][1], acc[1][3]);
        }
        bar_sync(1, 256);
        if (tid == 32) {
          sts32(pause, 0u);
          if (has_mid) mbar_arrive_relaxed(bars + 8 * (BAR_QGO + c));
        }
        if (tid < 16) {
          float4 a = sum8(redC + 4 * tid, 64);
          st_rlx4(&g_z[c][tid >> 3][kq][32 * cb + 4 * (tid & 7)], a.x, a.y, a.z, a.w, tag);
        }
        if (tid == 0) TLX(0, c * 16 + 8);
      }
    } else {
      const int b0i = has_mid ? c : NB - 2, b1i = has_mid ? c + 1 : NB - 1;
      __nv_bfloat16* xmid = xs + (b0i % 3) * 512;
      __nv_bfloat16* xpost = xs + (b1i % 3) * 512;
      uint2 bs;
      {
        CHAIN_IDS
        if (n == 0 && has_mid)
          bs = __ldg((const uint2*)(x + c * 512 + 4 * quad));
        else
          bs = *(const uint2*)((n ? xpost : xmid) + 4 * quad);
        mbar_wait(bars + 8 * (has_mid ? BAR_P1DONE + c : BAR_P2DONE + NB - 1), 0);
        if (tid == 0) TL(0, c * 16 + 2);
        __nanosleep(BDELAY);
        if (tid == 32) sts32(pause, 1u);
        const float* yp = &g_y[c][n][0][2 * quad];
        uint2 v[8];
        pollS<8, PS>(v, yp, 256, tag);
        if (tid == 0) TLX(0, c * 16 + 5);
        float a0 = ((bf_lo(v[0].x) + bf_lo(v[1].x)) + (bf_lo(v[2].x) + bf_lo(v[3].x))) + ((bf_lo(v[4].x) + bf_lo(v[5].x)) + (bf_lo(v[6].x) + bf_lo(v[7].x)));
        float a1 = ((bf_hi(v[0].x) + bf_hi(v[1].x)) + (bf_hi(v[2].x) + bf_hi(v[3].x))) + ((bf_hi(v[4].x) + bf_hi(v[5].x)) + (bf_hi(v[6].x) + bf_hi(v[7].x)));
        float a2 = ((bf_lo(v[0].y) + bf_lo(v[1].y)) + (bf_lo(v[2].y) + bf_lo(v[3].y))) + ((bf_lo(v[4].y) + bf_lo(v[5].y)) + (bf_lo(v[6].y) + bf_lo(v[7].y)));
        float a3 = ((bf_hi(v[0].y) + bf_hi(v[1].y)) + (bf_hi(v[2].y) + bf_hi(v[3].y))) + ((bf_hi(v[4].y) + bf_hi(v[5].y)) + (bf_hi(v[6].y) + bf_hi(v[7].y)));
        uint32_t p0 = pack_bf16(a0, a1), p1 = pack_bf16(a2, a3);
        p0 = pack_bf16(bf_lo(bs.x) + bf_lo(p0), bf_hi(bs.x) + bf_hi(p0));
        p1 = pack_bf16(bf_lo(bs.y) + bf_lo(p1), bf_hi(bs.y) + bf_hi(p1));
        bs = make_uint2(p0, p1);
        *(uint2*)((n ? xpost : xmid) + 4 * quad) = bs;
        bar_sync(1, 256);
        if (UB && tid == 32) sts32(pause, 0u);
        const __nv_bfloat16* xv = ((g8 & 1) ? xpost : xmid) + 64 * w + 4 * j;
        float acc[2][4] = {{0.f, 0.f, 0.f, 0.f}, {0.f, 0.f, 0.f, 0.f}}, sa[4] = {0.f, 0.f, 0.f, 0.f};
#pragma unroll
        for (int ks = 0; ks < 4; ks++) {
          uint2 t = *(const uint2*)(xv + 16 * ks);
          mma16816(acc[0], wb[ks][0][0], wb[ks][0][1], wb[ks][0][2], wb[ks][0][3], t.x, t.y);
          mma16816(acc[1], wb[ks][1][0], wb[ks][1][1], wb[ks][1][2], wb[ks][1][3], t.x, t.y);
          mma16816(sa, t.x, ones_row, t.y, ones_row, t.x, t.y);
        }
        if (j == 0) {
          *(float4*)&red1[w * 64 + 4 * g8] = make_float4(acc[0][0], acc[0][2], acc[1][0], acc[1][2]);
          *(float4*)&red1[w * 64 + 32 + 4 * g8] = make_float4(acc[0][1], acc[0][3], acc[1][1], acc[1][3]);
          if (g8 == 0) {
            stat[w * 4 + 0] = sa[0];
            stat[w * 4 + 1] = sa[2];
            stat[w * 4 + 3] = sa[3];
          }
          if (g8 == 1) stat[w * 4 + 2] = sa[1];
        }
        bar_sync(1, 256);
        if (w == 0 && i64 < 56) {
          float4 a = sum8(lane < 16 ? red1 + 4 * lane : stat, lane < 16 ? 64 : 4);
          float4 cs4 = *(const float4*)&csum[64 + 4 * (lane & 7)];
          float mb, rden;
          ln_consts(lane & 1 ? a.w : a.y, lane & 1 ? a.z : a.x, mb, rden);
          mb = __shfl_sync(0xffffffffu, mb, 16 + ((lane >> 3) & 1));
          rden = __shfl_sync(0xffffffffu, rden, 16 + ((lane >> 3) & 1));
          float h0 = rbf((a.x - mb * cs4.x) * rden), h1 = rbf((a.y - mb * cs4.y) * rden);
          float h2 = rbf((a.z - mb * cs4.z) * rden), h3 = rbf((a.w - mb * cs4.w) * rden);
          h0 = rbf(h0 * rcp_fast(1.f + ex2(-1.4426950408889634f * h0)));
          h1 = rbf(h1 * rcp_fast(1.f + ex2(-1.4426950408889634f * h1)));
          h2 = rbf(h2 * rcp_fast(1.f + ex2(-1.4426950408889634f * h2)));
          h3 = rbf(h3 * rcp_fast(1.f + ex2(-1.4426950408889634f * h3)));
          if (lane < 16) st_rlx4(&g_h[c][lane >> 3][32 * i64 + 4 * (lane & 7)], h0, h1, h2, h3, tag);
        }
        if (tid == 0) TLX(0, c * 16 + 6);
      }
      {
        CHAIN_IDS
        __nanosleep(DDELAY);
        if (tid == 32) sts32(pause, 1u);
        const bool active = (n == 0 && has_mid) || (has_post && (quad >> 1) == i64);
        if (active) {
          const float* zp = &g_z[c][n][0][4 * quad];
          uint4 v[4];
          poll1<4>(v, zp, 512, tag);
          float a0 = (u2f(v[0].x) + u2f(v[1].x)) + (u2f(v[2].x) + u2f(v[3].x));
          float a1 = (u2f(v[0].y) + u2f(v[1].y)) + (u2f(v[2].y) + u2f(v[3].y));
          float a2 = (u2f(v[0].z) + u2f(v[1].z)) + (u2f(v[2].z) + u2f(v[3].z));
          float a3 = (u2f(v[0].w) + u2f(v[1].w)) + (u2f(v[2].w) + u2f(v[3].w));
          uint32_t p0 = pack_bf16(a0, a1), p1 = pack_bf16(a2, a3);
          p0 = pack_bf16(bf_lo(bs.x) + bf_lo(p0), bf_hi(bs.x) + bf_hi(p0));
          p1 = pack_bf16(bf_lo(bs.y) + bf_lo(p1), bf_hi(bs.y) + bf_hi(p1));
          if (n == 0 && has_mid)
            *(uint2*)(xmid + 4 * quad) = make_uint2(p0, p1);
          else
            *(uint2*)(out + (has_mid ? c - 2 : NB - 2 + n) * 512 + 4 * quad) = make_uint2(p0, p1);
        }
        __syncwarp();
        if (tid == 0) TLX(0, c * 16 + 9);
        if (!has_mid) break;
        bar_sync(1, 256);
        const __nv_bfloat16* xv = xmid + 64 * w + 4 * j;
        float acc[4][4], sa[4] = {0.f, 0.f, 0.f, 0.f};
#pragma unroll
        for (int mt = 0; mt < 4; mt++)
#pragma unroll
          for (int i = 0; i < 4; i++) acc[mt][i] = 0.f;
#pragma unroll
        for (int ks = 0; ks < 4; ks++) {
          uint2 t = *(const uint2*)(xv + 16 * ks);
#pragma unroll
          for (int mt = 0; mt < 4; mt++) mma16816(acc[mt], wa[ks][mt][0], wa[ks][mt][1], wa[ks][mt][2], wa[ks][mt][3], t.x, t.y);
          mma16816(sa, t.x, ones_row, t.y, ones_row, t.x, t.y);
        }
        if (j == 0) {
#pragma unroll
          for (int mt = 0; mt < 4; mt++)
#pragma unroll
            for (int hf = 0; hf < 2; hf++) red1[w * 64 + q_lpos(8 * g8 + 2 * mt + hf)] = acc[mt][2 * hf];
          if (g8 == 0) *(float2*)&stat[w * 4] = make_float2(sa[0], sa[2]);
        }
        bar_sync(1, 256);
        if (w == 0) {
          float4 a = sum8(lane < 16 ? red1 + 4 * lane : stat, lane < 16 ? 64 : 4);
          float4 cs4 = *(const float4*)&csum[4 * (lane & 15)];
          float mb, rden;
          ln_consts(a.y, a.x, mb, rden);
          mb = __shfl_sync(0xffffffffu, mb, 16);
          rden = __shfl_sync(0xffffffffu, rden, 16);
          if (lane < 16)
            st_rlx4(&g_q[1][c][g][64 * hb + 4 * lane], rbf((a.x - mb * cs4.x) * rden), rbf((a.y - mb * cs4.y) * rden),
                    rbf((a.z - mb * cs4.z) * rden), rbf((a.w - mb * cs4.w) * rden), tag);
          if (tid == 0) TL(0, c * 16 + 10);
          if (tid == 0) mbar_arrive_relaxed(bars + 8 * (BAR_QGO + c));
        }
      }
    }
  }
}

__device__ __forceinline__ void producer_d(char* smem, int cta, const CUtensorMap* tm) {
  const uint32_t sbase = smem_u32(smem);
  const uint32_t bars = sbase + OFF_BAR;
  const uint32_t state = sbase + OFF_MISC;
  const uint32_t info = sbase + OFF_INFO;
  const int row0 = (cta >> 4) * 8192 + (cta & 15) * 512;
  uint64_t pol;
  asm volatile("createpolicy.fractional.L2::evict_first.b64 %0, 1.0;" : "=l"(pol));
  unsigned tnext = clock();
#pragma unroll 1
  for (int dn = 0; dn < NB * NT; dn++) {
    uint32_t st, bit, it = 0;
    while (true) {
      st = lds32(state);
      const uint32_t fr = st & ((1u << NSLOT) - 1);
      bit = fr & (0u - fr);
      if (bit && (int)(st >> 24) + LIM > dn && (!(st & ST_LOPEN) || fr != bit)) {
        uint32_t old;
        asm volatile("atom.relaxed.cta.shared::cta.and.b32 %0, [%1], %2;" : "=r"(old) : "r"(state), "r"(~bit) : "memory");
        if (old & bit) break;
      }
      __nanosleep(SPN);
      if (++it > (SPIN_LIMIT << 2)) __trap();
    }
    const int slot = __ffs(bit) - 1;
    const bool ret = (dn & 15) >= NT - RB && ((st >> 13) & 31) < ((st & ST_LOPEN) ? RMAX - RL : RMAX);
    const bool l2 = !ret && ((st >> 18) & 31) < L2MAX;
    if (ret || l2) state_add(state, ret ? ST_RET : ST_L2);
    sts8(info + dn, slot | (ret ? 0x80 : 0) | (l2 ? 0x40 : 0));
    const int h = 2 * dn;
    const uint32_t fb = bars + 8 * (BAR_FULLD + (h & 63));
    const int row = row0 + (dn >> 4) * 65536 + (dn & 15) * TK;
    const uint32_t dst = sbase + slot * TILE_BYTES;
    mbar_expect_tx(fb, HALF_BYTES);
    mbar_expect_tx(fb + 8, HALF_BYTES);
    if (h >= WD) mbar_wait(bars + 8 * (BAR_FULLD + ((h - WD) & 63)), ((h - WD) >> 6) & 1);
    pause_wait(state + 8);
    if (PACE) {
      unsigned now;
      while ((int)((now = clock()) - tnext) < 0) {}
      tnext = now + PACE;
    }
    tma_half(dst, tm, row, 0, fb, pol);
    if (l2) tma_prefetch(tm, row, 0);
    if (h + 1 >= WD) mbar_wait(bars + 8 * (BAR_FULLD + ((h + 1 - WD) & 63)), ((h + 1 - WD) >> 6) & 1);
    if (PACE) {
      unsigned now;
      while ((int)((now = clock()) - tnext) < 0) {}
      tnext = now + PACE;
    }
    tma_half(dst + HALF_BYTES, tm, row, 1, fb + 8, pol);
    if (l2) tma_prefetch(tm, row, 1);
    TL(3, dn);
  }
}

__device__ __forceinline__ void producer_l(char* smem, int cta, const CUtensorMap* tm) {
  const uint32_t sbase = smem_u32(smem);
  const uint32_t bars = sbase + OFF_BAR;
  const uint32_t state = sbase + OFF_MISC;
  const uint32_t info = sbase + OFF_INFO, linfo = info + NB * NT;
  const int row0 = (cta >> 4) * 8192 + (cta & 15) * 512;
  uint64_t pol;
  asm volatile("createpolicy.fractional.L2::evict_first.b64 %0, 1.0;" : "=l"(pol));
  uint32_t lpar = 0;
  unsigned tnext = clock();
  uint32_t lq[WL];
#pragma unroll
  for (int i = 0; i < WL; i++) lq[i] = 0;
#pragma unroll 1
  for (int lb = 0; lb < NB; lb++) {
    mbar_wait(bars + 8 * ((lb == NB - 1 ? BAR_P1DONE : BAR_LGO) + lb), 0);
    state_add(state, ST_LOPEN);
#pragma unroll 1
    for (int t = 0; t < NT; t++) {
      const uint32_t inf = lds8(info + lb * NT + t);
      if (inf & 0x80) continue;
      uint32_t bit, it = 0;
      while (true) {
        uint32_t fr = lds32(state) & ((1u << NSLOT) - 1);
        if (fr) {
          bit = 0x80000000u >> __clz(fr);
          uint32_t old;
          asm volatile("atom.relaxed.cta.shared::cta.and.b32 %0, [%1], %2;" : "=r"(old) : "r"(state), "r"(~bit) : "memory");
          if (old & bit) break;
        }
        __nanosleep(SPN);
        if (++it > (SPIN_LIMIT << 2)) __trap();
      }
      const int slot = __ffs(bit) - 1;
      sts8(linfo + lb * NT + t, slot);
      const int bi = (lb & 1) * NT + t;
      const uint32_t fb = bars + 8 * (BAR_FULLL + 2 * bi);
      const int row = row0 + lb * 65536 + t * TK;
      mbar_expect_tx(fb, HALF_BYTES);
      mbar_expect_tx(fb + 8, HALF_BYTES);
#pragma unroll
      for (int part = 0; part < 2; part++) {
        if (lq[0] && lb < NB - 1) mbar_wait(bars + 8 * (lq[0] & 0xff), (lq[0] >> 8) & 1);
        if (part == 0) pause_wait(state + 8);
        if (PACEL && lb < NB - 1) {
          unsigned now;
          while ((int)((now = clock()) - tnext) < 0) {}
          tnext = now + PACEL;
        }
        tma_half(sbase + slot * TILE_BYTES + part * HALF_BYTES, tm, row, part, fb + 8 * part, pol);
#pragma unroll
        for (int i = 0; i + 1 < WL; i++) lq[i] = lq[i + 1];
        lq[WL - 1] = (BAR_FULLL + 2 * bi + part) | (((lpar >> bi) & 1) << 8) | 0x200;
      }
      if (inf & 0x40) state_add(state, 0u - ST_L2);
      TL(3, 128 + lb * 16 + t);
      lpar ^= 1u << bi;
    }
    state_add(state, 0u - ST_LOPEN);
  }
}

__global__ void __launch_bounds__(NTHREADS, 1)
    fused_kernel(const __grid_constant__ CUtensorMap tm, uint32_t koff, const __nv_bfloat16* __restrict__ x,
                 const __nv_bfloat16* __restrict__ wq,
                 const __nv_bfloat16* __restrict__ wo, const __nv_bfloat16* __restrict__ w1,
                 const __nv_bfloat16* __restrict__ w2, __nv_bfloat16* __restrict__ out) {
  extern __shared__ __align__(1024) char smem[];
  const int tid = threadIdx.x, warp = tid >> 5, lane = tid & 31, cta = blockIdx.x;
  if (tid == 0) {
    const uint32_t sbase = smem_u32(smem);
    if (sbase & 1023) __trap();
    const uint32_t bars = sbase + OFF_BAR;
    for (int i = 0; i < 128; i++) mbar_init(bars + 8 * i, 1);
    for (int i = 0; i < 8; i++) {
      mbar_init(bars + 8 * (BAR_P1DONE + i), NW1);
      mbar_init(bars + 8 * (BAR_P2DONE + i), NW2);
      mbar_init(bars + 8 * (BAR_QGO + i), 1);
      mbar_init(bars + 8 * (BAR_LGO + i), NW2);
    }
    mbar_init(bars + 8 * BAR_Q1, NW1);
    uint32_t* misc = (uint32_t*)(smem + OFF_MISC);
    misc[0] = (1u << NSLOT) - 1;
    misc[2] = 0;
    misc[1] = *(volatile unsigned*)&g_epoch;
    asm volatile("fence.mbarrier_init.release.cluster;" ::: "memory");
  }
  __syncthreads();
  const unsigned epoch = ((const uint32_t*)(smem + OFF_MISC))[1];
  const uint32_t tag = epoch + 1;
  if (warp < 8) {
    asm volatile("setmaxnreg.inc.sync.aligned.u32 152;");
    chain_role(smem, tid, cta, tag, x, wq, wo, w1, w2, out);
    if (cta == 1 && tid == 0) *(volatile unsigned*)&g_epoch = epoch + 1;
  } else if (warp < 12) {
    asm volatile("setmaxnreg.dec.sync.aligned.u32 104;");
    if (warp < 8 + NW1) {
      attn_role<0, NW1>(smem, warp - 8, lane, cta, tag, koff);
    } else if (warp == 10) {
      if (lane == 0) producer_d(smem, cta, &tm);
    } else if (lane == 0) {
      producer_l(smem, cta, &tm);
    }
  } else {
    asm volatile("setmaxnreg.dec.sync.aligned.u32 104;");
    attn_role<1, NW2>(smem, warp - 12, lane, cta, tag, koff);
  }
}

typedef CUresult (*EncodeFn)(CUtensorMap*, CUtensorMapDataType, cuuint32_t, void*, const cuuint64_t*, const cuuint64_t*,
                             const cuuint32_t*, const cuuint32_t*, CUtensorMapInterleave, CUtensorMapSwizzle,
                             CUtensorMapL2promotion, CUtensorMapFloatOOBfill);

static_assert(SMEM_BYTES <= 232448, "smem");
}

extern "C" void kernel_launch(void* const* d_in, const int* in_sizes, int n_in, void* d_out, int out_size) {
  static EncodeFn enc = nullptr;
  if (!enc) {
    void* fn = nullptr;
    cudaDriverEntryPointQueryResult qr;
    cudaGetDriverEntryPoint("cuTensorMapEncodeTiled", &fn, cudaEnableDefault, &qr);
    enc = (EncodeFn)fn;
    cudaFuncSetAttribute(fused_kernel, cudaFuncAttributeMaxDynamicSharedMemorySize, SMEM_BYTES);
  }
  const __nv_bfloat16* x = (const __nv_bfloat16*)d_in[0];
  const __nv_bfloat16* kc = (const __nv_bfloat16*)d_in[1];
  const __nv_bfloat16* vc = (const __nv_bfloat16*)d_in[2];
  const __nv_bfloat16* wq = (const __nv_bfloat16*)d_in[3];
  const __nv_bfloat16* wo = (const __nv_bfloat16*)d_in[4];
  const __nv_bfloat16* w1 = (const __nv_bfloat16*)d_in[6];
  const __nv_bfloat16* w2 = (const __nv_bfloat16*)d_in[7];
  const bool kfirst = (const char*)kc < (const char*)vc;
  const char* lo = kfirst ? (const char*)kc : (const char*)vc;
  const char* hi = kfirst ? (const char*)vc : (const char*)kc;
  CUtensorMap tm;
  cuuint64_t dims[4] = {64, (cuuint64_t)8 * 8 * 8192, 2, 2};
  cuuint64_t strides[3] = {256, 128, (cuuint64_t)(hi - lo)};
  cuuint32_t box[4] = {64, TK, 2, 1};
  cuuint32_t es[4] = {1, 1, 1, 1};
  enc(&tm, CU_TENSOR_MAP_DATA_TYPE_BFLOAT16, 4, (void*)lo, dims, strides, box, es, CU_TENSOR_MAP_INTERLEAVE_NONE,
      CU_TENSOR_MAP_SWIZZLE_128B, CU_TENSOR_MAP_L2_PROMOTION_NONE, CU_TENSOR_MAP_FLOAT_OOB_FILL_NONE);
  fused_kernel<<<128, NTHREADS, SMEM_BYTES>>>(tm, kfirst ? 0u : (uint32_t)HALF_BYTES, x, wq, wo, w1, w2,
                                              (__nv_bfloat16*)d_out);
}
```

```cpp
#include <cuda_runtime.h>
#include <cuda.h>
#include <cuda_bf16.h>
#include <stdint.h>

namespace {

constexpr int NB = 8;
constexpr int NT = 16;
constexpr int TK = 32;
constexpr int NSLOT = 13;
#define RMAX_ 9
#define WD_ 3
#define WL_ 3
#define LIM_ 32
constexpr int LIM = LIM_;
#define PS_ 100
constexpr int PS = PS_;
#define L2MAX_ 19
constexpr int L2MAX = L2MAX_;
#define RL_ 0
constexpr int RL = RL_;
#define SPN_ 40
constexpr int SPN = SPN_;
#define A1_ 28
#define A2_ 22
#define WHI_ 4
#define WLOW_ 2
#define RB_ 9
constexpr int RB = RB_;
constexpr int RMAX = RMAX_;
constexpr int WD = WD_;
constexpr int WL = WL_;
constexpr int HALF_BYTES = TK * 256;
constexpr int TILE_BYTES = 2 * HALF_BYTES;
constexpr int PART_STRIDE = 272;
constexpr int NTHREADS = 512;
constexpr int NW1 = 2;
constexpr int NW2 = 4;
constexpr float SCALE_LOG2 = 0.08838834764831845f * 1.4426950408889634f;
constexpr unsigned SPIN_LIMIT = 1u << 24;

constexpr int OFF_MB1 = NSLOT * TILE_BYTES;
constexpr int OFF_MB2 = OFF_MB1 + 2048;
constexpr int OFF_ML1 = OFF_MB2 + 6144;
constexpr int OFF_ML2 = OFF_ML1 + 128;
constexpr int OFF_CH = OFF_ML2 + 128;
constexpr int OFF_REDA = OFF_CH, OFF_REDC = OFF_CH + 4096;
constexpr int OFF_XS = OFF_CH, OFF_RED1 = OFF_CH + 3072;
constexpr int OFF_STAT = OFF_CH + 5120;
constexpr int OFF_CSUM = OFF_STAT + 128;
constexpr int OFF_CH_END = OFF_CH + 6144;
constexpr int OFF_QS = OFF_CH_END;
constexpr int OFF_BAR = OFF_QS + 2048;
constexpr int OFF_INFO = OFF_BAR + 1344;
constexpr int OFF_MISC = OFF_INFO + 256;
constexpr int SMEM_BYTES = OFF_MISC + 32;
constexpr int BAR_FULLD = 0, BAR_FULLL = 64, BAR_P1DONE = 128, BAR_P2DONE = 136, BAR_QGO = 144, BAR_LGO = 152,
              BAR_Q1 = 160;
constexpr uint32_t ST_RET = 1u << 13, ST_L2 = 1u << 18, ST_LOPEN = 1u << 23, ST_DONE = 1u << 24;

__device__ __align__(16) float g_part[2][NB][128][PART_STRIDE];
__device__ __align__(16) float g_y[NB + 1][2][8][256];
__device__ __align__(16) float g_h[NB + 1][2][1792];
__device__ __align__(16) float g_z[NB + 1][2][4][512];
__device__ __align__(16) float g_q[2][NB][8][512];
__device__ unsigned g_epoch;
#define TL(role, idx)
#define TLX(role, idx)

__device__ __forceinline__ uint32_t smem_u32(const void* p) { return (uint32_t)__cvta_generic_to_shared(p); }
__device__ __forceinline__ void mbar_init(uint32_t bar, uint32_t cnt) {
  asm volatile("mbarrier.init.shared::cta.b64 [%0], %1;" ::"r"(bar), "r"(cnt));
}
__device__ __forceinline__ void mbar_arrive(uint32_t bar) {
  asm volatile("mbarrier.arrive.shared::cta.b64 _, [%0];" ::"r"(bar) : "memory");
}
__device__ __forceinline__ void mbar_arrive_relaxed(uint32_t bar) {
  asm volatile("mbarrier.arrive.relaxed.cta.shared::cta.b64 _, [%0];" ::"r"(bar) : "memory");
}
__device__ __forceinline__ void mbar_expect_tx(uint32_t bar, uint32_t bytes) {
  asm volatile("mbarrier.arrive.expect_tx.shared::cta.b64 _, [%0], %1;" ::"r"(bar), "r"(bytes) : "memory");
}
__device__ __forceinline__ void mbar_wait(uint32_t bar, uint32_t parity) {
  uint32_t ok, it = 0;
  do {
    asm volatile(
        "{\n.reg .pred p;\nmbarrier.try_wait.parity.shared::cta.b64 p, [%1], %2;\nselp.u32 %0, 1, 0, p;\n}"
        : "=r"(ok)
        : "r"(bar), "r"(parity)
        : "memory");
    if (++it > SPIN_LIMIT) __trap();
  } while (!ok);
}
__device__ __forceinline__ bool mbar_test(uint32_t bar, uint32_t parity) {
  uint32_t ok;
  asm volatile(
      "{\n.reg .pred p;\nmbarrier.test_wait.parity.shared::cta.b64 p, [%1], %2;\nselp.u32 %0, 1, 0, p;\n}"
      : "=r"(ok)
      : "r"(bar), "r"(parity)
      : "memory");
  return ok;
}
__device__ __forceinline__ void tma_half(uint32_t dst, const CUtensorMap* tm, int row, int part, uint32_t bar,
                                         uint64_t pol) {
  asm volatile(
      "cp.async.bulk.tensor.4d.shared::cluster.global.mbarrier::complete_tx::bytes.L2::cache_hint "
      "[%0], [%1, {%3, %4, %3, %6}], [%2], %5;" ::"r"(dst),
      "l"((uint64_t)tm), "r"(bar), "r"(0), "r"(row), "l"(pol), "r"(part)
      : "memory");
}
__device__ __forceinline__ void tma_prefetch(const CUtensorMap* tm, int row, int part) {
  asm volatile("cp.async.bulk.prefetch.tensor.4d.L2.global [%0, {%1, %2, %1, %3}];" ::"l"((uint64_t)tm), "r"(0), "r"(row),
               "r"(part)
               : "memory");
}
__device__ __forceinline__ void state_add(uint32_t addr, uint32_t v) {
  asm volatile("red.relaxed.cta.shared::cta.add.u32 [%0], %1;" ::"r"(addr), "r"(v) : "memory");
}
__device__ __forceinline__ uint32_t lds32(uint32_t addr) {
  uint32_t v;
  asm volatile("ld.volatile.shared::cta.u32 %0, [%1];" : "=r"(v) : "r"(addr) : "memory");
  return v;
}
__device__ __forceinline__ uint32_t lds8(uint32_t addr) {
  uint32_t v;
  asm volatile("ld.volatile.shared::cta.u8 %0, [%1];" : "=r"(v) : "r"(addr) : "memory");
  return v;
}
__device__ __forceinline__ void sts8(uint32_t addr, uint32_t v) {
  asm volatile("st.volatile.shared::cta.u8 [%0], %1;" ::"r"(addr), "r"(v) : "memory");
}
__device__ __forceinline__ void bar_sync(int id, int n) { asm volatile("bar.sync %0, %1;" ::"r"(id), "r"(n) : "memory"); }
__device__ __forceinline__ void mma16816(float (&d)[4], uint32_t a0, uint32_t a1, uint32_t a2, uint32_t a3, uint32_t b0,
                                         uint32_t b1) {
  asm("mma.sync.aligned.m16n8k16.row.col.f32.bf16.bf16.f32 {%0,%1,%2,%3}, {%4,%5,%6,%7}, {%8,%9}, {%0,%1,%2,%3};"
      : "+f"(d[0]), "+f"(d[1]), "+f"(d[2]), "+f"(d[3])
      : "r"(a0), "r"(a1), "r"(a2), "r"(a3), "r"(b0), "r"(b1));
}
__device__ __forceinline__ void ldsm4(uint32_t (&r)[4], uint32_t addr) {
  asm volatile("ldmatrix.sync.aligned.m8n8.x4.shared.b16 {%0,%1,%2,%3}, [%4];"
               : "=r"(r[0]), "=r"(r[1]), "=r"(r[2]), "=r"(r[3])
               : "r"(addr)
               : "memory");
}
__device__ __forceinline__ void ldsm4t(uint32_t (&r)[4], uint32_t addr) {
  asm volatile("ldmatrix.sync.aligned.m8n8.x4.trans.shared.b16 {%0,%1,%2,%3}, [%4];"
               : "=r"(r[0]), "=r"(r[1]), "=r"(r[2]), "=r"(r[3])
               : "r"(addr)
               : "memory");
}
__device__ __forceinline__ uint32_t movm(uint32_t a) {
  uint32_t d;
  asm volatile("movmatrix.sync.aligned.m8n8.trans.b16 %0, %1;" : "=r"(d) : "r"(a));
  return d;
}
__device__ __forceinline__ uint32_t pack_bf16(float lo, float hi) {
  uint32_t d;
  asm("cvt.rn.bf16x2.f32 %0, %1, %2;" : "=r"(d) : "f"(hi), "f"(lo));
  return d;
}
__device__ __forceinline__ float rbf(float x) { return __bfloat162float(__float2bfloat16_rn(x)); }
__device__ __forceinline__ float bf_lo(uint32_t v) { return __uint_as_float(v << 16); }
__device__ __forceinline__ float bf_hi(uint32_t v) { return __uint_as_float(v & 0xffff0000u); }
__device__ __forceinline__ float ex2(float x) {
  float y;
  asm("ex2.approx.ftz.f32 %0, %1;" : "=f"(y) : "f"(x));
  return y;
}
__device__ __forceinline__ uint4 ld_rlx4(const float* p) {
  uint4 v;
  asm volatile(
      "{\n.reg .b64 a, b;\nld.relaxed.gpu.global.v2.b64 {a, b}, [%4];\nmov.b64 {%0,%1}, a;\nmov.b64 {%2,%3}, b;\n}"
      : "=r"(v.x), "=r"(v.y), "=r"(v.z), "=r"(v.w)
      : "l"(p)
      : "memory");
  return v;
}
__device__ __forceinline__ uint32_t tagw(float f, uint32_t tag) { return (__float_as_uint(f) & ~1u) | tag; }
__device__ __forceinline__ void st_rlx4(float* p, float a, float b, float c, float d, uint32_t tag) {
  asm volatile(
      "{\n.reg .b64 a, b;\nmov.b64 a, {%1,%2};\nmov.b64 b, {%3,%4};\nst.relaxed.gpu.global.v2.b64 [%0], {a, b};\n}" ::"l"(p),
      "r"(tagw(a, tag)), "r"(__float_as_uint(b)), "r"(tagw(c, tag)), "r"(__float_as_uint(d))
      : "memory");
}
__device__ __forceinline__ void st_rlx_bf4(float* p, float a, float b, float c, float d, uint32_t tag) {
  uint32_t lo = (pack_bf16(a, b) & ~1u) | tag, hi = pack_bf16(c, d);
  asm volatile("{\n.reg .b64 a;\nmov.b64 a, {%1,%2};\nst.relaxed.gpu.global.b64 [%0], a;\n}" ::"l"(p), "r"(lo), "r"(hi)
               : "memory");
}
__device__ __forceinline__ uint32_t bad4(const uint4& v, uint32_t tag) { return (v.x ^ tag) | (v.z ^ tag); }
template <int N, int SLEEP>
__device__ __forceinline__ void poll(uint4 (&v)[N], const float* p, int stride, uint32_t tag) {
#pragma unroll
  for (int i = 0; i < N; i++) v[i] = ld_rlx4(p + i * stride);
  uint32_t it = 0;
  while (true) {
    uint32_t bad = 0;
#pragma unroll
    for (int i = 0; i < N; i++) bad |= bad4(v[i], tag);
    if (!(bad & 1)) break;
    if (SLEEP) __nanosleep(SLEEP);
#pragma unroll
    for (int i = 0; i < N; i++)
      if (bad4(v[i], tag) & 1) v[i] = ld_rlx4(p + i * stride);
    if (++it > SPIN_LIMIT) __trap();
  }
}
__device__ __forceinline__ uint2 ld_rlx2(const float* p);
__device__ __forceinline__ void ldp(uint4& v, const float* p) { v = ld_rlx4(p); }
__device__ __forceinline__ void ldp(uint2& v, const float* p) { v = ld_rlx2(p); }
__device__ __forceinline__ uint32_t badp(const uint4& v, uint32_t tag) { return bad4(v, tag); }
__device__ __forceinline__ uint32_t badp(const uint2& v, uint32_t tag) { return v.x ^ tag; }
template <int N, typename T>
__device__ __forceinline__ void poll1(T (&v)[N], const float* p, int stride, uint32_t tag) {
#pragma unroll
  for (int i = 0; i < N; i++) ldp(v[i], p + i * stride);
  uint32_t it = 0;
  while (true) {
    uint32_t bad = 0;
#pragma unroll
    for (int i = 0; i < N; i++) bad |= badp(v[i], tag);
    if (!(bad & 1)) break;
#pragma unroll
    for (int i = 0; i < N; i++)
      if (badp(v[i], tag) & 1) ldp(v[i], p + i * stride);
    if (++it > SPIN_LIMIT) __trap();
  }
}
template <int N, int SLEEP, typename T>
__device__ __forceinline__ void pollS(T (&v)[N], const float* p, int stride, uint32_t tag) {
#pragma unroll
  for (int i = 0; i < N; i++) ldp(v[i], p + i * stride);
  uint32_t it = 0;
  while (true) {
    uint32_t bad = 0;
#pragma unroll
    for (int i = 0; i < N; i++) bad |= badp(v[i], tag);
    if (!(bad & 1)) break;
    if (SLEEP) __nanosleep(SLEEP);
#pragma unroll
    for (int i = 0; i < N; i++)
      if (badp(v[i], tag) & 1) ldp(v[i], p + i * stride);
    if (++it > SPIN_LIMIT) __trap();
  }
}
__device__ __forceinline__ float rcp_fast(float x) {
  float y;
  asm("rcp.approx.ftz.f32 %0, %1;" : "=f"(y) : "f"(x));
  return y;
}
__device__ __forceinline__ float u2f(uint32_t u) { return __uint_as_float(u); }
__device__ __forceinline__ int opq(int v) {
  asm volatile("" : "+r"(v));
  return v;
}
__device__ __forceinline__ uint2 ld_rlx2(const float* p) {
  uint2 v;
  asm volatile("{\n.reg .b64 a;\nld.relaxed.gpu.global.b64 a, [%2];\nmov.b64 {%0,%1}, a;\n}"
               : "=r"(v.x), "=r"(v.y)
               : "l"(p)
               : "memory");
  return v;
}
__device__ __forceinline__ void sel_if(float& o, float v, int a, int b) {
  asm("{\n.reg .pred p;\nsetp.eq.s32 p, %2, %3;\nselp.f32 %0, %1, %0, p;\n}" : "+f"(o) : "f"(v), "r"(a), "r"(b));
}

__device__ __forceinline__ void ln_consts(float sx, float sxx, float& mb, float& rden) {
  float mean = sx * (1.f / 512.f);
  float var = fmaxf(fmaf(-mean, mean, sxx * (1.f / 512.f)), 0.f);
  mb = rbf(mean);
  float sq;
  asm("sqrt.approx.ftz.f32 %0, %1;" : "=f"(sq) : "f"(rbf(rbf(var) + 1e-5f)));
  rden = rcp_fast(rbf(sq));
}

struct AttnState {
  float acc[8][4];
  float m0, m1, l0, l1;
};

__device__ __forceinline__ void process_tile(uint32_t slot_addr, uint32_t kb, uint32_t vb, const uint32_t (&qf)[8][2],
                                             AttnState& st) {
  auto kaddr = [&](int i) { return slot_addr + (kb ^ (((i >> 1) & 3) << 5)) + (i >> 3) * 4096 + (i & 1) * 2048; };
  auto vaddr = [&](int i) { return slot_addr + (vb ^ ((i & 3) << 5)) + ((i >> 2) & 1) * 4096 + (i >> 3) * 2048; };
  uint32_t a[4][4];
  float sv[2][4];
#pragma unroll
  for (int kg = 0; kg < 2; kg++)
#pragma unroll
    for (int i = 0; i < 4; i++) sv[kg][i] = 0.f;
#pragma unroll
  for (int i = 0; i < 4; i++) ldsm4(a[i], kaddr(i));
#pragma unroll
  for (int i = 0; i < 16; i++) {
    mma16816(sv[i & 1], a[i & 3][0], a[i & 3][1], a[i & 3][2], a[i & 3][3], qf[i >> 1][0], qf[i >> 1][1]);
    if (i + 4 < 16) ldsm4(a[i & 3], kaddr(i + 4));
  }
#pragma unroll
  for (int i = 0; i < 4; i++) ldsm4t(a[i], vaddr(i));
  float t0 = fmaxf(fmaxf(sv[0][0], sv[0][2]), fmaxf(sv[1][0], sv[1][2]));
  float t1 = fmaxf(fmaxf(sv[0][1], sv[0][3]), fmaxf(sv[1][1], sv[1][3]));
#pragma unroll
  for (int o = 4; o < 32; o <<= 1) {
    t0 = fmaxf(t0, __shfl_xor_sync(0xffffffffu, t0, o));
    t1 = fmaxf(t1, __shfl_xor_sync(0xffffffffu, t1, o));
  }
  if (__any_sync(0xffffffffu, (t0 > st.m0) || (t1 > st.m1))) {
    float n0 = fmaxf(st.m0, t0), n1 = fmaxf(st.m1, t1);
    float a0 = ex2((st.m0 - n0) * SCALE_LOG2), a1 = ex2((st.m1 - n1) * SCALE_LOG2);
    st.m0 = n0;
    st.m1 = n1;
    st.l0 *= a0;
    st.l1 *= a1;
#pragma unroll
    for (int mt = 0; mt < 8; mt++) {
      st.acc[mt][0] *= a0;
      st.acc[mt][1] *= a1;
      st.acc[mt][2] *= a0;
      st.acc[mt][3] *= a1;
    }
  }
  const float c0 = -st.m0 * SCALE_LOG2, c1 = -st.m1 * SCALE_LOG2;
  uint32_t pb[2][2];
#pragma unroll
  for (int kg = 0; kg < 2; kg++) {
    float p0 = ex2(fmaf(sv[kg][0], SCALE_LOG2, c0));
    float p1 = ex2(fmaf(sv[kg][1], SCALE_LOG2, c1));
    float p2 = ex2(fmaf(sv[kg][2], SCALE_LOG2, c0));
    float p3 = ex2(fmaf(sv[kg][3], SCALE_LOG2, c1));
    st.l0 += p0 + p2;
    st.l1 += p1 + p3;
    pb[kg][0] = movm(pack_bf16(p0, p1));
    pb[kg][1] = movm(pack_bf16(p2, p3));
  }
#pragma unroll
  for (int i = 0; i < 16; i++) {
    mma16816(st.acc[i & 7], a[i & 3][0], a[i & 3][1], a[i & 3][2], a[i & 3][3], pb[i >> 3][0], pb[i >> 3][1]);
    if (i + 4 < 16) ldsm4t(a[i & 3], vaddr(i + 4));
  }
}

template <int SLEEP>
__device__ __forceinline__ void fetch_q(uint32_t (&qf)[8][2], const float* q, int lane, uint32_t tag) {
  const float* qp = q + ((lane >> 2) & 3) * 128 + (lane >> 4) * 64 + (lane & 3) * 16;
  uint4 v[4];
  if (SLEEP)
    poll<4, SLEEP>(v, qp, 4, tag);
  else
    poll1<4>(v, qp, 4, tag);
  __syncwarp();
#pragma unroll
  for (int u = 0; u < 4; u++) {
    uint32_t r0 = __byte_perm(v[u].x, v[u].y, 0x7632);
    uint32_t r1 = __byte_perm(v[u].z, v[u].w, 0x7632);
    uint32_t o0 = __shfl_down_sync(0xffffffffu, r0, 16);
    uint32_t o1 = __shfl_down_sync(0xffffffffu, r1, 16);
    bool lo = lane < 16;
    qf[u][0] = lo ? r0 : 0u;
    qf[u][1] = lo ? r1 : 0u;
    qf[4 + u][0] = lo ? o0 : 0u;
    qf[4 + u][1] = lo ? o1 : 0u;
  }
}

template <int LAYER, int NW>
__device__ __forceinline__ void attn_role(char* smem, int w_, int lane_, int cta_, uint32_t ep1, uint32_t koff) {
  const int w = w_, lane = lane_;
  const uint32_t tag = ep1 & 1;
  const uint32_t sbase = smem_u32(smem);
  const uint32_t bars = sbase + OFF_BAR;
  const uint32_t state = sbase + OFF_MISC;
  const uint32_t info = sbase + OFF_INFO, linfo = info + NB * NT;
  float* mbuf = (float*)(smem + (LAYER ? OFF_MB2 : OFF_MB1));
  float* mlbuf = (float*)(smem + (LAYER ? OFF_ML2 : OFF_ML1));
  const uint32_t x7 = lane & 7;
  const uint32_t kb = (x7 + 8 * ((lane >> 3) & 1)) * 128 + ((((uint32_t)lane >> 4) ^ x7) << 4) + koff;
  const uint32_t vb = (x7 + 8 * (lane >> 4)) * 128 + (((((uint32_t)lane >> 3) & 1) ^ x7) << 4) + (koff ^ HALF_BYTES);
  uint32_t lpar = 0;

#pragma unroll 1
  for (int b = 0; b < NB; b++) {
    uint32_t qf[8][2];
    {
      const int lane = opq(lane_), cta = opq(cta_);
      if (LAYER == 1) mbar_wait(bars + 8 * (BAR_QGO + b), 0);
      if (w == 0 && lane == 0) TL(1 + LAYER, b * 8 + 0);
      if (LAYER == 1 || b == 0) {
        fetch_q<LAYER ? 50 : 100>(qf, &g_q[LAYER][b][cta >> 4][0], lane, tag);
        if (lane == 0) mbar_arrive(bars + 8 * (LAYER == 0 ? BAR_Q1 : BAR_LGO + b));
      } else {
        const uint4* qs = (const uint4*)(smem + OFF_QS + (b & 1) * 1024 + (lane & 15) * 64);
#pragma unroll
        for (int u = 0; u < 4; u++) {
          uint4 t = lane < 16 ? qs[u] : make_uint4(0u, 0u, 0u, 0u);
          qf[2 * u][0] = t.x;
          qf[2 * u][1] = t.y;
          qf[2 * u + 1][0] = t.z;
          qf[2 * u + 1][1] = t.w;
        }
      }
    }
    if (w == 0 && lane == 0) TL(1 + LAYER, b * 8 + 1);
    AttnState st;
#pragma unroll
    for (int mt = 0; mt < 8; mt++)
#pragma unroll
      for (int i = 0; i < 4; i++) st.acc[mt][i] = 0.f;
    st.m0 = st.m1 = -INFINITY;
    st.l0 = st.l1 = 0.f;

    if (LAYER == 0) {
#pragma unroll 1
      for (int t = w; t < NT; t += NW) {
        const uint32_t fb = bars + 8 * (BAR_FULLD + ((b & 1) * NT + t) * 2);
        mbar_wait(fb, (b >> 1) & 1);
        mbar_wait(fb + 8, (b >> 1) & 1);
        uint32_t inf = lds8(info + b * NT + t);
        uint32_t slot = inf & 0x3f;
        process_tile(sbase + slot * TILE_BYTES, kb, vb, qf, st);
        __syncwarp();
        if (!(inf & 0x80) && lane == 0) state_add(state, 1u << slot);
        if (t == 8 && b + 1 < NB) {
          const int ln = opq(lane_);
          const float* qp = &g_q[0][b + 1][opq(cta_) >> 4][((ln >> 2) & 3) * 128 + (ln >> 4) * 64 + (ln & 3) * 16];
          uint4 v[4];
          poll<4, 100>(v, qp, 4, tag);
          uint4* qs = (uint4*)(smem + OFF_QS + ((b + 1) & 1) * 1024 + (ln & 15) * 64 + (ln >> 4) * 32);
          qs[0] = make_uint4(__byte_perm(v[0].x, v[0].y, 0x7632), __byte_perm(v[0].z, v[0].w, 0x7632),
                             __byte_perm(v[1].x, v[1].y, 0x7632), __byte_perm(v[1].z, v[1].w, 0x7632));
          qs[1] = make_uint4(__byte_perm(v[2].x, v[2].y, 0x7632), __byte_perm(v[2].z, v[2].w, 0x7632),
                             __byte_perm(v[3].x, v[3].y, 0x7632), __byte_perm(v[3].z, v[3].w, 0x7632));
          __syncwarp();
        }
      }
    } else {
#pragma unroll 1
      for (int i = 0; i < 2 * (NT / NW); i++) {
        int t = w + NW * (i % (NT / NW));
        uint32_t inf = lds8(info + b * NT + t);
        bool ret = inf & 0x80;
        if (ret != (i < NT / NW)) continue;
        uint32_t slot = inf & 0x3f;
        if (!ret) {
          int bi = (b & 1) * NT + t;
          mbar_wait(bars + 8 * (BAR_FULLL + 2 * bi), (lpar >> bi) & 1);
          mbar_wait(bars + 8 * (BAR_FULLL + 2 * bi + 1), (lpar >> bi) & 1);
          lpar ^= 1u << bi;
          slot = lds8(linfo + b * NT + t);
        }
        process_tile(sbase + slot * TILE_BYTES, kb, vb, qf, st);
        __syncwarp();
        if (lane == 0) state_add(state, (1u << slot) + ST_DONE - (ret ? ST_RET : 0u));
      }
    }

    if (lane == 0) TL(1 + LAYER, b * 8 + 2 + (w & 1));
    {
    const int lane = opq(lane_), w = opq(w_), cta = opq(cta_), g8 = lane >> 2, j = lane & 3;
    constexpr int OWN = 8 / NW;
#pragma unroll
    for (int o = 4; o < 32; o <<= 1) {
      st.l0 += __shfl_xor_sync(0xffffffffu, st.l0, o);
      st.l1 += __shfl_xor_sync(0xffffffffu, st.l1, o);
    }
    if (lane < 2) *(float4*)&mlbuf[w * 8 + lane * 4] = make_float4(st.m0, st.l0, st.m1, st.l1);
    if (j < 2) {
#pragma unroll
      for (int mt = 0; mt < 8; mt++) {
        int ow = mt / OWN;
        if (ow != w) {
          int sr = (w - ow - 1) & (NW - 1);
          *(float4*)&mbuf[(((ow * (NW - 1) + sr) * OWN + (mt % OWN)) * 16 + g8 * 2 + j) * 4] =
              make_float4(st.acc[mt][0], st.acc[mt][1], st.acc[mt][2], st.acc[mt][3]);
        }
      }
    }
    bar_sync(2 + LAYER, 32 * NW);
    if (j < 2) {
      float4 mlv[NW];
#pragma unroll
      for (int u = 0; u < NW; u++) mlv[u] = *(const float4*)&mlbuf[((w + u) & (NW - 1)) * 8 + j * 4];
      float M0 = mlv[0].x, M1 = mlv[0].z;
#pragma unroll
      for (int u = 1; u < NW; u++) {
        M0 = fmaxf(M0, mlv[u].x);
        M1 = fmaxf(M1, mlv[u].z);
      }
      float f0[NW], f1[NW], L0 = 0.f, L1 = 0.f;
#pragma unroll
      for (int u = 0; u < NW; u++) {
        f0[u] = ex2((mlv[u].x - M0) * SCALE_LOG2);
        f1[u] = ex2((mlv[u].z - M1) * SCALE_LOG2);
        L0 = fmaf(f0[u], mlv[u].y, L0);
        L1 = fmaf(f1[u], mlv[u].w, L1);
      }
      float* pp = &g_part[LAYER][b][cta][0];
#pragma unroll
      for (int e2 = 0; e2 < OWN / 2; e2++) {
        float o[2][4];
#pragma unroll
        for (int e1 = 0; e1 < 2; e1++) {
          const int e = 2 * e2 + e1;
          float o0 = 0.f, o1 = 0.f, o2 = 0.f, o3 = 0.f;
#pragma unroll
          for (int cw = 0; cw < NW; cw++) {
            sel_if(o0, st.acc[OWN * cw + e][0], w, cw);
            sel_if(o1, st.acc[OWN * cw + e][1], w, cw);
            sel_if(o2, st.acc[OWN * cw + e][2], w, cw);
            sel_if(o3, st.acc[OWN * cw + e][3], w, cw);
          }
          o0 *= f0[0];
          o1 *= f1[0];
          o2 *= f0[0];
          o3 *= f1[0];
#pragma unroll
          for (int sr = 0; sr < NW - 1; sr++) {
            float4 a = *(const float4*)&mbuf[(((w * (NW - 1) + sr) * OWN + e) * 16 + g8 * 2 + j) * 4];
            o0 = fmaf(a.x, f0[sr + 1], o0);
            o1 = fmaf(a.y, f1[sr + 1], o1);
            o2 = fmaf(a.z, f0[sr + 1], o2);
            o3 = fmaf(a.w, f1[sr + 1], o3);
          }
          o[e1][0] = o0;
          o[e1][1] = o1;
          o[e1][2] = o2;
          o[e1][3] = o3;
        }
        const int u = (OWN / 2) * w + e2;
        st_rlx_bf4(pp + (2 * j) * 64 + u * 16 + 2 * g8, o[0][0], o[0][2], o[1][0], o[1][2], tag);
        st_rlx_bf4(pp + (2 * j + 1) * 64 + u * 16 + 2 * g8, o[0][1], o[0][3], o[1][1], o[1][3], tag);
      }
      if (w == 0 && g8 == 0) st_rlx4(pp + 256 + 4 * j, M0, L0, M1, L1, tag);
    }
    __syncwarp();
    if (w == 0 && lane == 0) TL(1 + LAYER, b * 8 + 4);
    if (lane == 0) mbar_arrive_relaxed(bars + 8 * ((LAYER ? BAR_P2DONE : BAR_P1DONE) + b));
    bar_sync(2 + LAYER, 32 * NW);
    }
  }
}

constexpr uint32_t ONES2 = 0x3F803F80u;

template <int SLEEP>
__device__ __forceinline__ void attn_out(const float* part  , int g, int w, int lane, uint32_t tag,
                                         const uint32_t (&wa)[4][4][4], float* red) {
  const int g8 = lane >> 2, j = lane & 3;
  const float* base = part + (size_t)(16 * g + g8) * PART_STRIDE;
  const float* po = base + 32 * w + 4 * j;
  const float* pm = base + 256 + 2 * (w >> 1);
  uint2 ml0 = ld_rlx2(pm), ml1 = ld_rlx2(pm + 8 * PART_STRIDE);
  uint4 o4[2][2];
#pragma unroll
  for (int sg = 0; sg < 2; sg++)
#pragma unroll
    for (int u = 0; u < 2; u++) o4[sg][u] = ld_rlx4(po + sg * 8 * PART_STRIDE + 16 * u);
  uint32_t it = 0;
  while (true) {
    const uint32_t bad0 = (ml0.x ^ tag) | bad4(o4[0][0], tag) | bad4(o4[0][1], tag);
    const uint32_t bad1 = (ml1.x ^ tag) | bad4(o4[1][0], tag) | bad4(o4[1][1], tag);
    if (!((bad0 | bad1) & 1)) break;
    if (SLEEP) __nanosleep(SLEEP);
    if (bad0 & 1) {
      ml0 = ld_rlx2(pm);
      o4[0][0] = ld_rlx4(po);
      o4[0][1] = ld_rlx4(po + 16);
    }
    if (bad1 & 1) {
      ml1 = ld_rlx2(pm + 8 * PART_STRIDE);
      o4[1][0] = ld_rlx4(po + 8 * PART_STRIDE);
      o4[1][1] = ld_rlx4(po + 8 * PART_STRIDE + 16);
    }
    if (++it > SPIN_LIMIT) __trap();
  }
  __syncwarp();
  float M = fmaxf(u2f(ml0.x), u2f(ml1.x));
#pragma unroll
  for (int o = 4; o < 32; o <<= 1) M = fmaxf(M, __shfl_xor_sync(0xffffffffu, M, o));
  float fo0 = ex2((u2f(ml0.x) - M) * SCALE_LOG2), fo1 = ex2((u2f(ml1.x) - M) * SCALE_LOG2);
  float L = fmaf(fo0, u2f(ml0.y), fo1 * u2f(ml1.y));
#pragma unroll
  for (int o = 4; o < 32; o <<= 1) L += __shfl_xor_sync(0xffffffffu, L, o);
  const float inv = rcp_fast(L);
  fo0 *= inv;
  fo1 *= inv;
  float y[8];
#pragma unroll
  for (int sg = 0; sg < 2; sg++) {
    float acc[4][4];
#pragma unroll
    for (int mt = 0; mt < 4; mt++)
#pragma unroll
      for (int i = 0; i < 4; i++) acc[mt][i] = 0.f;
#pragma unroll
    for (int ks = 0; ks < 4; ks++) {
      const uint32_t b0 = (ks & 1) ? o4[sg][ks >> 1].z : o4[sg][ks >> 1].x;
      const uint32_t b1 = (ks & 1) ? o4[sg][ks >> 1].w : o4[sg][ks >> 1].y;
#pragma unroll
      for (int mt = 0; mt < 4; mt++) mma16816(acc[mt], wa[ks][mt][0], wa[ks][mt][1], wa[ks][mt][2], wa[ks][mt][3], b0, b1);
    }
    const float f0 = __shfl_sync(0xffffffffu, sg ? fo1 : fo0, 8 * j);
    const float f1 = __shfl_sync(0xffffffffu, sg ? fo1 : fo0, 8 * j + 4);
#pragma unroll
    for (int mt = 0; mt < 4; mt++)
#pragma unroll
      for (int hf = 0; hf < 2; hf++) {
        const float t = fmaf(f0, acc[mt][2 * hf], f1 * acc[mt][2 * hf + 1]);
        y[2 * mt + hf] = sg ? y[2 * mt + hf] + t : t;
      }
  }
#pragma unroll
  for (int o = 1; o < 4; o <<= 1) {
#pragma unroll
    for (int i = 0; i < 8; i++) y[i] += __shfl_xor_sync(0xffffffffu, y[i], o);
  }
  if (j == 0) {
    *(float4*)&red[8 * g8] = make_float4(y[0], y[1], y[2], y[3]);
    *(float4*)&red[8 * g8 + 4] = make_float4(y[4], y[5], y[6], y[7]);
  }
}

__device__ __forceinline__ int q_lpos(int c) {
  int kk = c >> 4, r = c & 15;
  return ((r & 7) >> 1) * 16 + kk * 4 + (r & 1) + 2 * (r >> 3);
}

__device__ __forceinline__ float4 sum8(const float* p, int stride) {
  float4 a = *(const float4*)p;
#pragma unroll
  for (int u = 1; u < 8; u++) {
    float4 t = *(const float4*)(p + u * stride);
    a.x += t.x;
    a.y += t.y;
    a.z += t.z;
    a.w += t.w;
  }
  return a;
}

#define CHAIN_IDS                                                                                             \
  const int tid = opq(tid_), cta = opq(cta_);                                                                 \
  const int w = tid >> 5, lane = tid & 31, g8 = lane >> 2, j = lane & 3;                                      \
  const int g = cta >> 4, hb = (cta & 15) >> 1, i64 = g * 8 + hb, cb = i64 & 15, kq = i64 >> 4;               \
  const int n = tid >> 7, quad = tid & 127;                                                                   \
  const uint32_t ones_row = g8 == 0 ? ONES2 : 0u;                                                             \
  (void)w, (void)lane, (void)g8, (void)j, (void)g, (void)hb, (void)i64, (void)cb, (void)kq, (void)n, (void)quad, \
      (void)ones_row;

template <typename F>
__device__ __forceinline__ void load_wa(uint32_t (&wa)[4][4][4], const __nv_bfloat16* base, int pitch, F rowf) {
#pragma unroll
  for (int ks = 0; ks < 4; ks++) {
    uint4 r[4];
#pragma unroll
    for (int e = 0; e < 4; e++) r[e] = __ldg((const uint4*)(base + (size_t)rowf(ks, e) * pitch));
    const uint32_t c0[4] = {r[0].x, r[0].y, r[0].z, r[0].w}, c1[4] = {r[1].x, r[1].y, r[1].z, r[1].w};
    const uint32_t c2[4] = {r[2].x, r[2].y, r[2].z, r[2].w}, c3[4] = {r[3].x, r[3].y, r[3].z, r[3].w};
#pragma unroll
    for (int mt = 0; mt < 4; mt++) {
      wa[ks][mt][0] = __byte_perm(c0[mt], c1[mt], 0x5410);
      wa[ks][mt][1] = __byte_perm(c0[mt], c1[mt], 0x7632);
      wa[ks][mt][2] = __byte_perm(c2[mt], c3[mt], 0x5410);
      wa[ks][mt][3] = __byte_perm(c2[mt], c3[mt], 0x7632);
    }
  }
}

__device__ __forceinline__ void chain_role(char* smem, int tid_, int cta_, uint32_t ep1, const __nv_bfloat16* __restrict__ x,
                                           const __nv_bfloat16* __restrict__ wq, const __nv_bfloat16* __restrict__ wo,
                                           const __nv_bfloat16* __restrict__ w1, const __nv_bfloat16* __restrict__ w2,
                                           __nv_bfloat16* __restrict__ out) {
  const uint32_t sbase = smem_u32(smem);
  const uint32_t bars = sbase + OFF_BAR;
  const uint32_t tag = ep1 & 1;
  const bool set1 = cta_ & 1;
  __nv_bfloat16* xs = (__nv_bfloat16*)(smem + OFF_XS);
  float* redA = (float*)(smem + OFF_REDA);
  float* redC = (float*)(smem + OFF_REDC);
  float* red1 = (float*)(smem + OFF_RED1);
  float* stat = (float*)(smem + OFF_STAT);
  float* csum = (float*)(smem + OFF_CSUM);

  uint32_t wa[4][4][4];
  uint32_t wb[4][2][4];

  if (set1) {
    {
      CHAIN_IDS
      const uint4* xp = (const uint4*)x;
      uint4 x0 = __ldg(xp + tid), x1 = __ldg(xp + tid + 256);
      load_wa(wa, wq + 512 * g + 64 * hb + 8 * g8, 4096, [&](int ks, int e) { return 64 * w + 16 * ks + 4 * j + e; });
      uint4* xn = (uint4*)(smem + OFF_MB1);
      xn[tid] = x0;
      xn[tid + 256] = x1;
    }
    bar_sync(1, 256);
    {
      CHAIN_IDS
      float c[4][4], cs[4][4], sa[4] = {0.f, 0.f, 0.f, 0.f};
#pragma unroll
      for (int mt = 0; mt < 4; mt++)
#pragma unroll
        for (int i = 0; i < 4; i++) c[mt][i] = cs[mt][i] = 0.f;
#pragma unroll
      for (int ks = 0; ks < 4; ks++) {
        uint2 bv = *(const uint2*)(smem + OFF_MB1 + (g8 * 512 + 64 * w + 16 * ks + 4 * j) * 2);
#pragma unroll
        for (int mt = 0; mt < 4; mt++) {
          mma16816(c[mt], wa[ks][mt][0], wa[ks][mt][1], wa[ks][mt][2], wa[ks][mt][3], bv.x, bv.y);
          mma16816(cs[mt], wa[ks][mt][0], wa[ks][mt][1], wa[ks][mt][2], wa[ks][mt][3], ONES2, ONES2);
        }
        mma16816(sa, bv.x, ones_row, bv.y, ones_row, bv.x, bv.y);
      }
      float* st16 = (float*)(smem + OFF_XS);
      if (j == 0) {
#pragma unroll
        for (int mt = 0; mt < 4; mt++)
#pragma unroll
          for (int hf = 0; hf < 2; hf++) red1[w * 64 + q_lpos(8 * g8 + 2 * mt + hf)] = cs[mt][2 * hf];
      }
      if (j == (g8 >> 1)) st16[w * 16 + g8] = (g8 & 1) ? sa[1] : sa[0];
      if (g8 == 0) {
        st16[w * 16 + 8 + 2 * j] = sa[2];
        st16[w * 16 + 8 + 2 * j + 1] = sa[3];
      }
      float* rb = (float*)(smem + OFF_MB1);
#pragma unroll
      for (int rnd = 0; rnd < 2; rnd++) {
        bar_sync(1, 256);
        if ((j >> 1) == rnd) {
#pragma unroll
          for (int mt = 0; mt < 4; mt++)
#pragma unroll
            for (int hf = 0; hf < 2; hf++) {
              const int lp = q_lpos(8 * g8 + 2 * mt + hf);
              rb[(w * 4 + 2 * (j & 1)) * 64 + lp] = c[mt][2 * hf];
              rb[(w * 4 + 2 * (j & 1) + 1) * 64 + lp] = c[mt][2 * hf + 1];
            }
        }
        bar_sync(1, 256);
        if (tid < 64) {
          const int nl = tid >> 4, qd = tid & 15, nb = 4 * rnd + nl;
          float4 a = sum8(rb + nl * 64 + 4 * qd, 256);
          float4 cs4 = sum8(red1 + 4 * qd, 64);
          float sxx = 0.f, sx = 0.f;
#pragma unroll
          for (int u = 0; u < 8; u++) {
            sxx += st16[u * 16 + nb];
            sx += st16[u * 16 + 8 + nb];
          }
          float mb, rden;
          ln_consts(sx, sxx, mb, rden);
          st_rlx4(&g_q[0][nb][g][64 * hb + 4 * qd], rbf((a.x - mb * cs4.x) * rden), rbf((a.y - mb * cs4.y) * rden),
                  rbf((a.z - mb * cs4.z) * rden), rbf((a.w - mb * cs4.w) * rden), tag);
          if (nb == 0) *(float4*)&csum[4 * qd] = cs4;
        }
      }
      if (tid == 0) TL(0, 200);
    }
  }
  mbar_wait(bars + 8 * BAR_Q1, 0);
  {
    CHAIN_IDS
    if (!set1)
      load_wa(wa, wo + (size_t)512 * g * 512 + 64 * hb + 8 * g8, 512, [&](int ks, int e) {
        const int p = 64 * w + 32 * (ks >> 1) + 8 * j + 4 * (ks & 1) + e;
        const int pp = p & 127;
        return (p & ~127) + (pp >> 5) * 32 + ((pp >> 1) & 1) * 16 + ((pp & 31) >> 2) + 8 * (pp & 1);
      });
    const __nv_bfloat16* bp = set1 ? w1 + 32 * i64 + 4 * g8 : w2 + (size_t)448 * kq * 512 + 32 * cb + 4 * g8;
    const int pitch = set1 ? 1792 : 512;
    const bool valid = set1 ? i64 < 56 : w < 7;
    uint2 r[4][4];
#pragma unroll
    for (int ks = 0; ks < 4; ks++)
#pragma unroll
      for (int e = 0; e < 4; e++)
        r[ks][e] = valid ? __ldg((const uint2*)(bp + (size_t)(64 * w + 16 * ks + 4 * j + e) * pitch)) : make_uint2(0u, 0u);
#pragma unroll
    for (int ks = 0; ks < 4; ks++) {
      wb[ks][0][0] = __byte_perm(r[ks][0].x, r[ks][1].x, 0x5410);
      wb[ks][0][1] = __byte_perm(r[ks][0].x, r[ks][1].x, 0x7632);
      wb[ks][0][2] = __byte_perm(r[ks][2].x, r[ks][3].x, 0x5410);
      wb[ks][0][3] = __byte_perm(r[ks][2].x, r[ks][3].x, 0x7632);
      wb[ks][1][0] = __byte_perm(r[ks][0].y, r[ks][1].y, 0x5410);
      wb[ks][1][1] = __byte_perm(r[ks][0].y, r[ks][1].y, 0x7632);
      wb[ks][1][2] = __byte_perm(r[ks][2].y, r[ks][3].y, 0x5410);
      wb[ks][1][3] = __byte_perm(r[ks][2].y, r[ks][3].y, 0x7632);
    }
    bar_sync(1, 256);
    if (set1) {
      float cs[2][4] = {{0.f, 0.f, 0.f, 0.f}, {0.f, 0.f, 0.f, 0.f}};
#pragma unroll
      for (int ks = 0; ks < 4; ks++) {
        mma16816(cs[0], wb[ks][0][0], wb[ks][0][1], wb[ks][0][2], wb[ks][0][3], ONES2, ONES2);
        mma16816(cs[1], wb[ks][1][0], wb[ks][1][1], wb[ks][1][2], wb[ks][1][3], ONES2, ONES2);
      }
      if (j == 0) *(float4*)&red1[w * 32 + 4 * g8] = make_float4(cs[0][0], cs[0][2], cs[1][0], cs[1][2]);
      *(uint2*)(xs + 512 + 4 * tid) = make_uint2(0u, 0u);
    } else {
      if (tid < 128) *(float4*)&redA[(tid >> 4) * 128 + 64 + 4 * (tid & 15)] = make_float4(0.f, 0.f, 0.f, 0.f);
    }
    bar_sync(1, 256);
    if (set1 && tid < 8) *(float4*)&csum[64 + 4 * tid] = sum8(red1 + 4 * tid, 32);
    if (tid == 0) TL(0, 201);
  }

#pragma unroll 1
  for (int c = 0; c <= NB; c++) {
    const bool has_mid = c < NB, has_post = c >= 2;
    if (!set1) {
      {
        CHAIN_IDS
        if (has_post) {
          mbar_wait(bars + 8 * (BAR_P2DONE + c - 2), 0);
          if (tid == 0) TLX(0, c * 16 + 0);
          attn_out<300>(&g_part[1][c - 2][0][0], g, w, lane, tag, wa, redA + w * 128 + (has_mid ? 64 : 0));
          if (tid == 0) TLX(0, c * 16 + 1);
        }
        mbar_wait(bars + 8 * (has_mid ? BAR_P1DONE + c : BAR_P2DONE + NB - 1), 0);
        if (tid == 0) TL(0, c * 16 + 2);
        attn_out<PS>(has_mid ? &g_part[0][c][0][0] : &g_part[1][NB - 1][0][0], g, w, lane, tag, wa,
                     redA + w * 128 + (has_mid ? 0 : 64));
        if (tid == 0) TLX(0, c * 16 + 3);
        bar_sync(1, 256);
        if (tid < 32) {
          float4 a = sum8(redA + 4 * tid, 128);
          st_rlx_bf4(&g_y[c][tid >> 4][g][32 * hb + 2 * (tid & 15)], a.x, a.y, a.z, a.w, tag);
        }
        if (tid == 0) TLX(0, c * 16 + 4);
      }
      {
        CHAIN_IDS
        float acc[2][4] = {{0.f, 0.f, 0.f, 0.f}, {0.f, 0.f, 0.f, 0.f}};
        if (w < 7) {
          const float* hp = &g_h[c][g8 & 1][448 * kq + 64 * w + 4 * j];
          uint4 v[4];
          if (g8 < 2) {
            poll1<4>(v, hp, 16, tag);
          } else {
#pragma unroll
            for (int u = 0; u < 4; u++) v[u] = make_uint4(0u, 0u, 0u, 0u);
          }
          __syncwarp();
          if (tid == 0) TLX(0, c * 16 + 7);
#pragma unroll
          for (int ks = 0; ks < 4; ks++) {
            const uint32_t b0 = __byte_perm(v[ks].x, v[ks].y, 0x7632), b1 = __byte_perm(v[ks].z, v[ks].w, 0x7632);
            mma16816(acc[0], wb[ks][0][0], wb[ks][0][1], wb[ks][0][2], wb[ks][0][3], b0, b1);
            mma16816(acc[1], wb[ks][1][0], wb[ks][1][1], wb[ks][1][2], wb[ks][1][3], b0, b1);
          }
        }
        if (j == 0) {
          *(float4*)&redC[w * 64 + 4 * g8] = make_float4(acc[0][0], acc[0][2], acc[1][0], acc[1][2]);
          *(float4*)&redC[w * 64 + 32 + 4 * g8] = make_float4(acc[0][1], acc[0][3], acc[1][1], acc[1][3]);
        }
        bar_sync(1, 256);
        if (tid == 32 && has_mid) mbar_arrive_relaxed(bars + 8 * (BAR_QGO + c));
        if (tid < 16) {
          float4 a = sum8(redC + 4 * tid, 64);
          st_rlx4(&g_z[c][tid >> 3][kq][32 * cb + 4 * (tid & 7)], a.x, a.y, a.z, a.w, tag);
        }
        if (tid == 0) TLX(0, c * 16 + 8);
      }
    } else {
      const int b0i = has_mid ? c : NB - 2, b1i = has_mid ? c + 1 : NB - 1;
      __nv_bfloat16* xmid = xs + (b0i % 3) * 512;
      __nv_bfloat16* xpost = xs + (b1i % 3) * 512;
      uint2 bs;
      {
        CHAIN_IDS
        if (n == 0 && has_mid)
          bs = __ldg((const uint2*)(x + c * 512 + 4 * quad));
        else
          bs = *(const uint2*)((n ? xpost : xmid) + 4 * quad);
        mbar_wait(bars + 8 * (has_mid ? BAR_P1DONE + c : BAR_P2DONE + NB - 1), 0);
        if (tid == 0) TL(0, c * 16 + 2);
        const float* yp = &g_y[c][n][0][2 * quad];
        uint2 v[8];
        pollS<8, PS>(v, yp, 256, tag);
        if (tid == 0) TLX(0, c * 16 + 5);
        float a0 = ((bf_lo(v[0].x) + bf_lo(v[1].x)) + (bf_lo(v[2].x) + bf_lo(v[3].x))) + ((bf_lo(v[4].x) + bf_lo(v[5].x)) + (bf_lo(v[6].x) + bf_lo(v[7].x)));
        float a1 = ((bf_hi(v[0].x) + bf_hi(v[1].x)) + (bf_hi(v[2].x) + bf_hi(v[3].x))) + ((bf_hi(v[4].x) + bf_hi(v[5].x)) + (bf_hi(v[6].x) + bf_hi(v[7].x)));
        float a2 = ((bf_lo(v[0].y) + bf_lo(v[1].y)) + (bf_lo(v[2].y) + bf_lo(v[3].y))) + ((bf_lo(v[4].y) + bf_lo(v[5].y)) + (bf_lo(v[6].y) + bf_lo(v[7].y)));
        float a3 = ((bf_hi(v[0].y) + bf_hi(v[1].y)) + (bf_hi(v[2].y) + bf_hi(v[3].y))) + ((bf_hi(v[4].y) + bf_hi(v[5].y)) + (bf_hi(v[6].y) + bf_hi(v[7].y)));
        uint32_t p0 = pack_bf16(a0, a1), p1 = pack_bf16(a2, a3);
        p0 = pack_bf16(bf_lo(bs.x) + bf_lo(p0), bf_hi(bs.x) + bf_hi(p0));
        p1 = pack_bf16(bf_lo(bs.y) + bf_lo(p1), bf_hi(bs.y) + bf_hi(p1));
        bs = make_uint2(p0, p1);
        *(uint2*)((n ? xpost : xmid) + 4 * quad) = bs;
        bar_sync(1, 256);
        const __nv_bfloat16* xv = ((g8 & 1) ? xpost : xmid) + 64 * w + 4 * j;
        float acc[2][4] = {{0.f, 0.f, 0.f, 0.f}, {0.f, 0.f, 0.f, 0.f}}, sa[4] = {0.f, 0.f, 0.f, 0.f};
#pragma unroll
        for (int ks = 0; ks < 4; ks++) {
          uint2 t = *(const uint2*)(xv + 16 * ks);
          mma16816(acc[0], wb[ks][0][0], wb[ks][0][1], wb[ks][0][2], wb[ks][0][3], t.x, t.y);
          mma16816(acc[1], wb[ks][1][0], wb[ks][1][1], wb[ks][1][2], wb[ks][1][3], t.x, t.y);
          mma16816(sa, t.x, ones_row, t.y, ones_row, t.x, t.y);
        }
        if (j == 0) {
          *(float4*)&red1[w * 64 + 4 * g8] = make_float4(acc[0][0], acc[0][2], acc[1][0], acc[1][2]);
          *(float4*)&red1[w * 64 + 32 + 4 * g8] = make_float4(acc[0][1], acc[0][3], acc[1][1], acc[1][3]);
          if (g8 == 0) {
            stat[w * 4 + 0] = sa[0];
            stat[w * 4 + 1] = sa[2];
            stat[w * 4 + 3] = sa[3];
          }
          if (g8 == 1) stat[w * 4 + 2] = sa[1];
        }
        bar_sync(1, 256);
        if (w == 0 && i64 < 56) {
          float4 a = sum8(lane < 16 ? red1 + 4 * lane : stat, lane < 16 ? 64 : 4);
          float4 cs4 = *(const float4*)&csum[64 + 4 * (lane & 7)];
          float mb, rden;
          ln_consts(lane & 1 ? a.w : a.y, lane & 1 ? a.z : a.x, mb, rden);
          mb = __shfl_sync(0xffffffffu, mb, 16 + ((lane >> 3) & 1));
          rden = __shfl_sync(0xffffffffu, rden, 16 + ((lane >> 3) & 1));
          float h0 = rbf((a.x - mb * cs4.x) * rden), h1 = rbf((a.y - mb * cs4.y) * rden);
          float h2 = rbf((a.z - mb * cs4.z) * rden), h3 = rbf((a.w - mb * cs4.w) * rden);
          h0 = rbf(h0 * rcp_fast(1.f + ex2(-1.4426950408889634f * h0)));
          h1 = rbf(h1 * rcp_fast(1.f + ex2(-1.4426950408889634f * h1)));
          h2 = rbf(h2 * rcp_fast(1.f + ex2(-1.4426950408889634f * h2)));
          h3 = rbf(h3 * rcp_fast(1.f + ex2(-1.4426950408889634f * h3)));
          if (lane < 16) st_rlx4(&g_h[c][lane >> 3][32 * i64 + 4 * (lane & 7)], h0, h1, h2, h3, tag);
        }
        if (tid == 0) TLX(0, c * 16 + 6);
      }
      {
        CHAIN_IDS
        const bool active = (n == 0 && has_mid) || (has_post && (quad >> 1) == i64);
        if (active) {
          const float* zp = &g_z[c][n][0][4 * quad];
          uint4 v[4];
          poll1<4>(v, zp, 512, tag);
          float a0 = (u2f(v[0].x) + u2f(v[1].x)) + (u2f(v[2].x) + u2f(v[3].x));
          float a1 = (u2f(v[0].y) + u2f(v[1].y)) + (u2f(v[2].y) + u2f(v[3].y));
          float a2 = (u2f(v[0].z) + u2f(v[1].z)) + (u2f(v[2].z) + u2f(v[3].z));
          float a3 = (u2f(v[0].w) + u2f(v[1].w)) + (u2f(v[2].w) + u2f(v[3].w));
          uint32_t p0 = pack_bf16(a0, a1), p1 = pack_bf16(a2, a3);
          p0 = pack_bf16(bf_lo(bs.x) + bf_lo(p0), bf_hi(bs.x) + bf_hi(p0));
          p1 = pack_bf16(bf_lo(bs.y) + bf_lo(p1), bf_hi(bs.y) + bf_hi(p1));
          if (n == 0 && has_mid)
            *(uint2*)(xmid + 4 * quad) = make_uint2(p0, p1);
          else
            *(uint2*)(out + (has_mid ? c - 2 : NB - 2 + n) * 512 + 4 * quad) = make_uint2(p0, p1);
        }
        __syncwarp();
        if (tid == 0) TLX(0, c * 16 + 9);
        if (!has_mid) break;
        bar_sync(1, 256);
        const __nv_bfloat16* xv = xmid + 64 * w + 4 * j;
        float acc[4][4], sa[4] = {0.f, 0.f, 0.f, 0.f};
#pragma unroll
        for (int mt = 0; mt < 4; mt++)
#pragma unroll
          for (int i = 0; i < 4; i++) acc[mt][i] = 0.f;
#pragma unroll
        for (int ks = 0; ks < 4; ks++) {
          uint2 t = *(const uint2*)(xv + 16 * ks);
#pragma unroll
          for (int mt = 0; mt < 4; mt++) mma16816(acc[mt], wa[ks][mt][0], wa[ks][mt][1], wa[ks][mt][2], wa[ks][mt][3], t.x, t.y);
          mma16816(sa, t.x, ones_row, t.y, ones_row, t.x, t.y);
        }
        if (j == 0) {
#pragma unroll
          for (int mt = 0; mt < 4; mt++)
#pragma unroll
            for (int hf = 0; hf < 2; hf++) red1[w * 64 + q_lpos(8 * g8 + 2 * mt + hf)] = acc[mt][2 * hf];
          if (g8 == 0) *(float2*)&stat[w * 4] = make_float2(sa[0], sa[2]);
        }
        bar_sync(1, 256);
        if (w == 0) {
          float4 a = sum8(lane < 16 ? red1 + 4 * lane : stat, lane < 16 ? 64 : 4);
          float4 cs4 = *(const float4*)&csum[4 * (lane & 15)];
          float mb, rden;
          ln_consts(a.y, a.x, mb, rden);
          mb = __shfl_sync(0xffffffffu, mb, 16);
          rden = __shfl_sync(0xffffffffu, rden, 16);
          if (lane < 16)
            st_rlx4(&g_q[1][c][g][64 * hb + 4 * lane], rbf((a.x - mb * cs4.x) * rden), rbf((a.y - mb * cs4.y) * rden),
                    rbf((a.z - mb * cs4.z) * rden), rbf((a.w - mb * cs4.w) * rden), tag);
          if (tid == 0) TL(0, c * 16 + 10);
          if (tid == 0) mbar_arrive_relaxed(bars + 8 * (BAR_QGO + c));
        }
      }
    }
  }
}

__device__ __forceinline__ void producer_d(char* smem, int cta, const CUtensorMap* tm) {
  const uint32_t sbase = smem_u32(smem);
  const uint32_t bars = sbase + OFF_BAR;
  const uint32_t state = sbase + OFF_MISC;
  const uint32_t info = sbase + OFF_INFO;
  const int row0 = (cta >> 4) * 8192 + (cta & 15) * 512;
  uint64_t pol;
  asm volatile("createpolicy.fractional.L2::evict_first.b64 %0, 1.0;" : "=l"(pol));
#pragma unroll 1
  for (int dn = 0; dn < NB * NT; dn++) {
    uint32_t st, bit, it = 0;
    while (true) {
      st = lds32(state);
      const uint32_t fr = st & ((1u << NSLOT) - 1);
      bit = fr & (0u - fr);
      if (bit && (int)(st >> 24) + LIM > dn && (!(st & ST_LOPEN) || fr != bit)) {
        uint32_t old;
        asm volatile("atom.relaxed.cta.shared::cta.and.b32 %0, [%1], %2;" : "=r"(old) : "r"(state), "r"(~bit) : "memory");
        if (old & bit) break;
      }
      __nanosleep(SPN);
      if (++it > (SPIN_LIMIT << 2)) __trap();
    }
    const int slot = __ffs(bit) - 1;
    const bool ret = (dn & 15) >= NT - RB && ((st >> 13) & 31) < ((st & ST_LOPEN) ? RMAX - RL : RMAX);
    const bool l2 = !ret && ((st >> 18) & 31) < L2MAX;
    if (ret || l2) state_add(state, ret ? ST_RET : ST_L2);
    sts8(info + dn, slot | (ret ? 0x80 : 0) | (l2 ? 0x40 : 0));
    const int ahead = dn - (int)(st >> 24);
    const int wd = ahead >= A1_ ? WLOW_ : ahead >= A2_ ? WD : WHI_;
    const int h = 2 * dn;
    const uint32_t fb = bars + 8 * (BAR_FULLD + (h & 63));
    const int row = row0 + (dn >> 4) * 65536 + (dn & 15) * TK;
    const uint32_t dst = sbase + slot * TILE_BYTES;
    mbar_expect_tx(fb, HALF_BYTES);
    mbar_expect_tx(fb + 8, HALF_BYTES);
    if (h >= wd) mbar_wait(bars + 8 * (BAR_FULLD + ((h - wd) & 63)), ((h - wd) >> 6) & 1);
    tma_half(dst, tm, row, 0, fb, pol);
    if (l2) tma_prefetch(tm, row, 0);
    if (h + 1 >= wd) mbar_wait(bars + 8 * (BAR_FULLD + ((h + 1 - wd) & 63)), ((h + 1 - wd) >> 6) & 1);
    tma_half(dst + HALF_BYTES, tm, row, 1, fb + 8, pol);
    if (l2) tma_prefetch(tm, row, 1);
    TL(3, dn);
  }
}

__device__ __forceinline__ void producer_l(char* smem, int cta, const CUtensorMap* tm) {
  const uint32_t sbase = smem_u32(smem);
  const uint32_t bars = sbase + OFF_BAR;
  const uint32_t state = sbase + OFF_MISC;
  const uint32_t info = sbase + OFF_INFO, linfo = info + NB * NT;
  const int row0 = (cta >> 4) * 8192 + (cta & 15) * 512;
  uint64_t pol;
  asm volatile("createpolicy.fractional.L2::evict_first.b64 %0, 1.0;" : "=l"(pol));
  uint32_t lpar = 0;
  uint32_t lq[WL];
#pragma unroll
  for (int i = 0; i < WL; i++) lq[i] = 0;
#pragma unroll 1
  for (int lb = 0; lb < NB; lb++) {
    mbar_wait(bars + 8 * ((lb == NB - 1 ? BAR_P1DONE : BAR_LGO) + lb), 0);
    state_add(state, ST_LOPEN);
#pragma unroll 1
    for (int t = 0; t < NT; t++) {
      const uint32_t inf = lds8(info + lb * NT + t);
      if (inf & 0x80) continue;
      uint32_t bit, it = 0;
      while (true) {
        uint32_t fr = lds32(state) & ((1u << NSLOT) - 1);
        if (fr) {
          bit = 0x80000000u >> __clz(fr);
          uint32_t old;
          asm volatile("atom.relaxed.cta.shared::cta.and.b32 %0, [%1], %2;" : "=r"(old) : "r"(state), "r"(~bit) : "memory");
          if (old & bit) break;
        }
        __nanosleep(SPN);
        if (++it > (SPIN_LIMIT << 2)) __trap();
      }
      const int slot = __ffs(bit) - 1;
      sts8(linfo + lb * NT + t, slot);
      const int bi = (lb & 1) * NT + t;
      const uint32_t fb = bars + 8 * (BAR_FULLL + 2 * bi);
      const int row = row0 + lb * 65536 + t * TK;
      mbar_expect_tx(fb, HALF_BYTES);
      mbar_expect_tx(fb + 8, HALF_BYTES);
#pragma unroll
      for (int part = 0; part < 2; part++) {
        if (lq[0] && lb < NB - 1) mbar_wait(bars + 8 * (lq[0] & 0xff), (lq[0] >> 8) & 1);
        tma_half(sbase + slot * TILE_BYTES + part * HALF_BYTES, tm, row, part, fb + 8 * part, pol);
#pragma unroll
        for (int i = 0; i + 1 < WL; i++) lq[i] = lq[i + 1];
        lq[WL - 1] = (BAR_FULLL + 2 * bi + part) | (((lpar >> bi) & 1) << 8) | 0x200;
      }
      if (inf & 0x40) state_add(state, 0u - ST_L2);
      TL(3, 128 + lb * 16 + t);
      lpar ^= 1u << bi;
    }
    state_add(state, 0u - ST_LOPEN);
  }
}

__global__ void __launch_bounds__(NTHREADS, 1)
    fused_kernel(const __grid_constant__ CUtensorMap tm, uint32_t koff, const __nv_bfloat16* __restrict__ x,
                 const __nv_bfloat16* __restrict__ wq,
                 const __nv_bfloat16* __restrict__ wo, const __nv_bfloat16* __restrict__ w1,
                 const __nv_bfloat16* __restrict__ w2, __nv_bfloat16* __restrict__ out) {
  extern __shared__ __align__(1024) char smem[];
  const int tid = threadIdx.x, warp = tid >> 5, lane = tid & 31, cta = blockIdx.x;
  if (tid == 0) {
    const uint32_t sbase = smem_u32(smem);
    if (sbase & 1023) __trap();
    const uint32_t bars = sbase + OFF_BAR;
    for (int i = 0; i < 128; i++) mbar_init(bars + 8 * i, 1);
    for (int i = 0; i < 8; i++) {
      mbar_init(bars + 8 * (BAR_P1DONE + i), NW1);
      mbar_init(bars + 8 * (BAR_P2DONE + i), NW2);
      mbar_init(bars + 8 * (BAR_QGO + i), 1);
      mbar_init(bars + 8 * (BAR_LGO + i), NW2);
    }
    mbar_init(bars + 8 * BAR_Q1, NW1);
    uint32_t* misc = (uint32_t*)(smem + OFF_MISC);
    misc[0] = (1u << NSLOT) - 1;
    misc[1] = *(volatile unsigned*)&g_epoch;
    asm volatile("fence.mbarrier_init.release.cluster;" ::: "memory");
  }
  __syncthreads();
  const unsigned epoch = ((const uint32_t*)(smem + OFF_MISC))[1];
  const uint32_t tag = epoch + 1;
  if (warp < 8) {
    asm volatile("setmaxnreg.inc.sync.aligned.u32 152;");
    chain_role(smem, tid, cta, tag, x, wq, wo, w1, w2, out);
    if (cta == 1 && tid == 0) *(volatile unsigned*)&g_epoch = epoch + 1;
  } else if (warp < 12) {
    asm volatile("setmaxnreg.dec.sync.aligned.u32 104;");
    if (warp < 8 + NW1) {
      attn_role<0, NW1>(smem, warp - 8, lane, cta, tag, koff);
    } else if (warp == 10) {
      if (lane == 0) producer_d(smem, cta, &tm);
    } else if (lane == 0) {
      producer_l(smem, cta, &tm);
    }
  } else {
    asm volatile("setmaxnreg.dec.sync.aligned.u32 104;");
    attn_role<1, NW2>(smem, warp - 12, lane, cta, tag, koff);
  }
}

typedef CUresult (*EncodeFn)(CUtensorMap*, CUtensorMapDataType, cuuint32_t, void*, const cuuint64_t*, const cuuint64_t*,
                             const cuuint32_t*, const cuuint32_t*, CUtensorMapInterleave, CUtensorMapSwizzle,
                             CUtensorMapL2promotion, CUtensorMapFloatOOBfill);

static_assert(SMEM_BYTES <= 232448, "smem");
}

extern "C" void kernel_launch(void* const* d_in, const int* in_sizes, int n_in, void* d_out, int out_size) {
  static EncodeFn enc = nullptr;
  if (!enc) {
    void* fn = nullptr;
    cudaDriverEntryPointQueryResult qr;
    cudaGetDriverEntryPoint("cuTensorMapEncodeTiled", &fn, cudaEnableDefault, &qr);
    enc = (EncodeFn)fn;
    cudaFuncSetAttribute(fused_kernel, cudaFuncAttributeMaxDynamicSharedMemorySize, SMEM_BYTES);
  }
  const __nv_bfloat16* x = (const __nv_bfloat16*)d_in[0];
  const __nv_bfloat16* kc = (const __nv_bfloat16*)d_in[1];
  const __nv_bfloat16* vc = (const __nv_bfloat16*)d_in[2];
  const __nv_bfloat16* wq = (const __nv_bfloat16*)d_in[3];
  const __nv_bfloat16* wo = (const __nv_bfloat16*)d_in[4];
  const __nv_bfloat16* w1 = (const __nv_bfloat16*)d_in[6];
  const __nv_bfloat16* w2 = (const __nv_bfloat16*)d_in[7];
  const bool kfirst = (const char*)kc < (const char*)vc;
  const char* lo = kfirst ? (const char*)kc : (const char*)vc;
  const char* hi = kfirst ? (const char*)vc : (const char*)kc;
  CUtensorMap tm;
  cuuint64_t dims[4] = {64, (cuuint64_t)8 * 8 * 8192, 2, 2};
  cuuint64_t strides[3] = {256, 128, (cuuint64_t)(hi - lo)};
  cuuint32_t box[4] = {64, TK, 2, 1};
  cuuint32_t es[4] = {1, 1, 1, 1};
  enc(&tm, CU_TENSOR_MAP_DATA_TYPE_BFLOAT16, 4, (void*)lo, dims, strides, box, es, CU_TENSOR_MAP_INTERLEAVE_NONE,
      CU_TENSOR_MAP_SWIZZLE_128B, CU_TENSOR_MAP_L2_PROMOTION_NONE, CU_TENSOR_MAP_FLOAT_OOB_FILL_NONE);
  fused_kernel<<<128, NTHREADS, SMEM_BYTES>>>(tm, kfirst ? 0u : (uint32_t)HALF_BYTES, x, wq, wo, w1, w2,
                                              (__nv_bfloat16*)d_out);
}
```

```cpp
#include <cuda_runtime.h>
#include <cuda.h>
#include <cuda_bf16.h>
#include <stdint.h>

namespace {

constexpr int NB = 8;
constexpr int NT = 16;
constexpr int TK = 32;
constexpr int NSLOT = 13;
#define RMAX_ 10
#define WD_ 3
#define WL_ 3
#define LIM_ 33
constexpr int LIM = LIM_;
#define PS_ 100
constexpr int PS = PS_;
#define L2MAX_ 18
constexpr int L2MAX = L2MAX_;
#define RL_ 0
constexpr int RL = RL_;
#define SPN_ 40
constexpr int SPN = SPN_;
#define A1_ 28
#define A2_ 22
#define WHI_ 4
#define WLOW_ 2
#define RB_ 9
constexpr int RB = RB_;
constexpr int RMAX = RMAX_;
constexpr int WD = WD_;
constexpr int WL = WL_;
constexpr int HALF_BYTES = TK * 256;
constexpr int TILE_BYTES = 2 * HALF_BYTES;
constexpr int PART_STRIDE = 272;
constexpr int NTHREADS = 512;
constexpr int NW1 = 2;
constexpr int NW2 = 4;
constexpr float SCALE_LOG2 = 0.08838834764831845f * 1.4426950408889634f;
constexpr unsigned SPIN_LIMIT = 1u << 24;

constexpr int OFF_MB1 = NSLOT * TILE_BYTES;
constexpr int OFF_MB2 = OFF_MB1 + 2048;
constexpr int OFF_ML1 = OFF_MB2 + 6144;
constexpr int OFF_ML2 = OFF_ML1 + 128;
constexpr int OFF_CH = OFF_ML2 + 128;
constexpr int OFF_REDA = OFF_CH, OFF_REDC = OFF_CH + 4096;
constexpr int OFF_XS = OFF_CH, OFF_RED1 = OFF_CH + 3072;
constexpr int OFF_STAT = OFF_CH + 5120;
constexpr int OFF_CSUM = OFF_STAT + 128;
constexpr int OFF_CH_END = OFF_CH + 6144;
constexpr int OFF_QS = OFF_CH_END;
constexpr int OFF_BAR = OFF_QS + 2048;
constexpr int OFF_INFO = OFF_BAR + 1344;
constexpr int OFF_MISC = OFF_INFO + 256;
constexpr int SMEM_BYTES = OFF_MISC + 32;
constexpr int BAR_FULLD = 0, BAR_FULLL = 64, BAR_P1DONE = 128, BAR_P2DONE = 136, BAR_QGO = 144, BAR_LGO = 152,
              BAR_Q1 = 160;
constexpr uint32_t ST_RET = 1u << 13, ST_L2 = 1u << 18, ST_LOPEN = 1u << 23, ST_DONE = 1u << 24;

__device__ __align__(16) float g_part[2][NB][128][PART_STRIDE];
__device__ __align__(16) float g_y[NB + 1][2][8][256];
__device__ __align__(16) float g_h[NB + 1][2][1792];
__device__ __align__(16) float g_z[NB + 1][2][4][512];
__device__ __align__(16) float g_q[2][NB][8][512];
__device__ unsigned g_epoch;
#define TL(role, idx)
#define TLX(role, idx)

__device__ __forceinline__ uint32_t smem_u32(const void* p) { return (uint32_t)__cvta_generic_to_shared(p); }
__device__ __forceinline__ void mbar_init(uint32_t bar, uint32_t cnt) {
  asm volatile("mbarrier.init.shared::cta.b64 [%0], %1;" ::"r"(bar), "r"(cnt));
}
__device__ __forceinline__ void mbar_arrive(uint32_t bar) {
  asm volatile("mbarrier.arrive.shared::cta.b64 _, [%0];" ::"r"(bar) : "memory");
}
__device__ __forceinline__ void mbar_arrive_relaxed(uint32_t bar) {
  asm volatile("mbarrier.arrive.relaxed.cta.shared::cta.b64 _, [%0];" ::"r"(bar) : "memory");
}
__device__ __forceinline__ void mbar_expect_tx(uint32_t bar, uint32_t bytes) {
  asm volatile("mbarrier.arrive.expect_tx.shared::cta.b64 _, [%0], %1;" ::"r"(bar), "r"(bytes) : "memory");
}
__device__ __forceinline__ void mbar_wait(uint32_t bar, uint32_t parity) {
  uint32_t ok, it = 0;
  do {
    asm volatile(
        "{\n.reg .pred p;\nmbarrier.try_wait.parity.shared::cta.b64 p, [%1], %2;\nselp.u32 %0, 1, 0, p;\n}"
        : "=r"(ok)
        : "r"(bar), "r"(parity)
        : "memory");
    if (++it > SPIN_LIMIT) __trap();
  } while (!ok);
}
__device__ __forceinline__ void tma_half(uint32_t dst, const CUtensorMap* tm, int row, int part, uint32_t bar,
                                         uint64_t pol) {
  asm volatile(
      "cp.async.bulk.tensor.4d.shared::cluster.global.mbarrier::complete_tx::bytes.L2::cache_hint "
      "[%0], [%1, {%3, %4, %3, %6}], [%2], %5;" ::"r"(dst),
      "l"((uint64_t)tm), "r"(bar), "r"(0), "r"(row), "l"(pol), "r"(part)
      : "memory");
}
__device__ __forceinline__ void tma_prefetch(const CUtensorMap* tm, int row, int part) {
  asm volatile("cp.async.bulk.prefetch.tensor.4d.L2.global [%0, {%1, %2, %1, %3}];" ::"l"((uint64_t)tm), "r"(0), "r"(row),
               "r"(part)
               : "memory");
}
__device__ __forceinline__ void state_add(uint32_t addr, uint32_t v) {
  asm volatile("red.relaxed.cta.shared::cta.add.u32 [%0], %1;" ::"r"(addr), "r"(v) : "memory");
}
__device__ __forceinline__ uint32_t lds32(uint32_t addr) {
  uint32_t v;
  asm volatile("ld.volatile.shared::cta.u32 %0, [%1];" : "=r"(v) : "r"(addr) : "memory");
  return v;
}
__device__ __forceinline__ uint32_t lds8(uint32_t addr) {
  uint32_t v;
  asm volatile("ld.volatile.shared::cta.u8 %0, [%1];" : "=r"(v) : "r"(addr) : "memory");
  return v;
}
__device__ __forceinline__ void sts8(uint32_t addr, uint32_t v) {
  asm volatile("st.volatile.shared::cta.u8 [%0], %1;" ::"r"(addr), "r"(v) : "memory");
}
__device__ __forceinline__ void bar_sync(int id, int n) { asm volatile("bar.sync %0, %1;" ::"r"(id), "r"(n) : "memory"); }
__device__ __forceinline__ void mma16816(float (&d)[4], uint32_t a0, uint32_t a1, uint32_t a2, uint32_t a3, uint32_t b0,
                                         uint32_t b1) {
  asm("mma.sync.aligned.m16n8k16.row.col.f32.bf16.bf16.f32 {%0,%1,%2,%3}, {%4,%5,%6,%7}, {%8,%9}, {%0,%1,%2,%3};"
      : "+f"(d[0]), "+f"(d[1]), "+f"(d[2]), "+f"(d[3])
      : "r"(a0), "r"(a1), "r"(a2), "r"(a3), "r"(b0), "r"(b1));
}
__device__ __forceinline__ void ldsm4(uint32_t (&r)[4], uint32_t addr) {
  asm volatile("ldmatrix.sync.aligned.m8n8.x4.shared.b16 {%0,%1,%2,%3}, [%4];"
               : "=r"(r[0]), "=r"(r[1]), "=r"(r[2]), "=r"(r[3])
               : "r"(addr)
               : "memory");
}
__device__ __forceinline__ void ldsm4t(uint32_t (&r)[4], uint32_t addr) {
  asm volatile("ldmatrix.sync.aligned.m8n8.x4.trans.shared.b16 {%0,%1,%2,%3}, [%4];"
               : "=r"(r[0]), "=r"(r[1]), "=r"(r[2]), "=r"(r[3])
               : "r"(addr)
               : "memory");
}
__device__ __forceinline__ uint32_t movm(uint32_t a) {
  uint32_t d;
  asm volatile("movmatrix.sync.aligned.m8n8.trans.b16 %0, %1;" : "=r"(d) : "r"(a));
  return d;
}
__device__ __forceinline__ uint32_t pack_bf16(float lo, float hi) {
  uint32_t d;
  asm("cvt.rn.bf16x2.f32 %0, %1, %2;" : "=r"(d) : "f"(hi), "f"(lo));
  return d;
}
__device__ __forceinline__ float rbf(float x) { return __bfloat162float(__float2bfloat16_rn(x)); }
__device__ __forceinline__ float bf_lo(uint32_t v) { return __uint_as_float(v << 16); }
__device__ __forceinline__ float bf_hi(uint32_t v) { return __uint_as_float(v & 0xffff0000u); }
__device__ __forceinline__ float ex2(float x) {
  float y;
  asm("ex2.approx.ftz.f32 %0, %1;" : "=f"(y) : "f"(x));
  return y;
}
__device__ __forceinline__ uint4 ld_rlx4(const float* p) {
  uint4 v;
  asm volatile(
      "{\n.reg .b64 a, b;\nld.relaxed.gpu.global.v2.b64 {a, b}, [%4];\nmov.b64 {%0,%1}, a;\nmov.b64 {%2,%3}, b;\n}"
      : "=r"(v.x), "=r"(v.y), "=r"(v.z), "=r"(v.w)
      : "l"(p)
      : "memory");
  return v;
}
__device__ __forceinline__ uint32_t tagw(float f, uint32_t tag) { return (__float_as_uint(f) & ~1u) | tag; }
__device__ __forceinline__ void st_rlx4(float* p, float a, float b, float c, float d, uint32_t tag) {
  asm volatile(
      "{\n.reg .b64 a, b;\nmov.b64 a, {%1,%2};\nmov.b64 b, {%3,%4};\nst.relaxed.gpu.global.v2.b64 [%0], {a, b};\n}" ::"l"(p),
      "r"(tagw(a, tag)), "r"(__float_as_uint(b)), "r"(tagw(c, tag)), "r"(__float_as_uint(d))
      : "memory");
}
__device__ __forceinline__ void st_rlx_bf4(float* p, float a, float b, float c, float d, uint32_t tag) {
  uint32_t lo = (pack_bf16(a, b) & ~1u) | tag, hi = pack_bf16(c, d);
  asm volatile("{\n.reg .b64 a;\nmov.b64 a, {%1,%2};\nst.relaxed.gpu.global.b64 [%0], a;\n}" ::"l"(p), "r"(lo), "r"(hi)
               : "memory");
}
__device__ __forceinline__ uint32_t bad4(const uint4& v, uint32_t tag) { return (v.x ^ tag) | (v.z ^ tag); }
template <int N, int SLEEP>
__device__ __forceinline__ void poll(uint4 (&v)[N], const float* p, int stride, uint32_t tag) {
#pragma unroll
  for (int i = 0; i < N; i++) v[i] = ld_rlx4(p + i * stride);
  uint32_t it = 0;
  while (true) {
    uint32_t bad = 0;
#pragma unroll
    for (int i = 0; i < N; i++) bad |= bad4(v[i], tag);
    if (!(bad & 1)) break;
    if (SLEEP) __nanosleep(SLEEP);
#pragma unroll
    for (int i = 0; i < N; i++)
      if (bad4(v[i], tag) & 1) v[i] = ld_rlx4(p + i * stride);
    if (++it > SPIN_LIMIT) __trap();
  }
}
__device__ __forceinline__ uint2 ld_rlx2(const float* p);
__device__ __forceinline__ void ldp(uint4& v, const float* p) { v = ld_rlx4(p); }
__device__ __forceinline__ void ldp(uint2& v, const float* p) { v = ld_rlx2(p); }
__device__ __forceinline__ uint32_t badp(const uint4& v, uint32_t tag) { return bad4(v, tag); }
__device__ __forceinline__ uint32_t badp(const uint2& v, uint32_t tag) { return v.x ^ tag; }
template <int N, typename T>
__device__ __forceinline__ void poll1(T (&v)[N], const float* p, int stride, uint32_t tag) {
#pragma unroll
  for (int i = 0; i < N; i++) ldp(v[i], p + i * stride);
  uint32_t it = 0;
  while (true) {
    uint32_t bad = 0;
#pragma unroll
    for (int i = 0; i < N; i++) bad |= badp(v[i], tag);
    if (!(bad & 1)) break;
#pragma unroll
    for (int i = 0; i < N; i++)
      if (badp(v[i], tag) & 1) ldp(v[i], p + i * stride);
    if (++it > SPIN_LIMIT) __trap();
  }
}
template <int N, int SLEEP, typename T>
__device__ __forceinline__ void pollS(T (&v)[N], const float* p, int stride, uint32_t tag) {
#pragma unroll
  for (int i = 0; i < N; i++) ldp(v[i], p + i * stride);
  uint32_t it = 0;
  while (true) {
    uint32_t bad = 0;
#pragma unroll
    for (int i = 0; i < N; i++) bad |= badp(v[i], tag);
    if (!(bad & 1)) break;
    if (SLEEP) __nanosleep(SLEEP);
#pragma unroll
    for (int i = 0; i < N; i++)
      if (badp(v[i], tag) & 1) ldp(v[i], p + i * stride);
    if (++it > SPIN_LIMIT) __trap();
  }
}
__device__ __forceinline__ float rcp_fast(float x) {
  float y;
  asm("rcp.approx.ftz.f32 %0, %1;" : "=f"(y) : "f"(x));
  return y;
}
__device__ __forceinline__ float u2f(uint32_t u) { return __uint_as_float(u); }
__device__ __forceinline__ int opq(int v) {
  asm volatile("" : "+r"(v));
  return v;
}
__device__ __forceinline__ uint2 ld_rlx2(const float* p) {
  uint2 v;
  asm volatile("{\n.reg .b64 a;\nld.relaxed.gpu.global.b64 a, [%2];\nmov.b64 {%0,%1}, a;\n}"
               : "=r"(v.x), "=r"(v.y)
               : "l"(p)
               : "memory");
  return v;
}
__device__ __forceinline__ void sel_if(float& o, float v, int a, int b) {
  asm("{\n.reg .pred p;\nsetp.eq.s32 p, %2, %3;\nselp.f32 %0, %1, %0, p;\n}" : "+f"(o) : "f"(v), "r"(a), "r"(b));
}

__device__ __forceinline__ void ln_consts(float sx, float sxx, float& mb, float& rden) {
  float mean = sx * (1.f / 512.f);
  float var = fmaxf(fmaf(-mean, mean, sxx * (1.f / 512.f)), 0.f);
  mb = rbf(mean);
  float sq;
  asm("sqrt.approx.ftz.f32 %0, %1;" : "=f"(sq) : "f"(rbf(rbf(var) + 1e-5f)));
  rden = rcp_fast(rbf(sq));
}

struct AttnState {
  float acc[8][4];
  float m0, m1, l0, l1;
};

__device__ __forceinline__ void process_tile(uint32_t slot_addr, uint32_t kb, uint32_t vb, const uint32_t (&qf)[8][2],
                                             AttnState& st) {
  auto kaddr = [&](int i) { return slot_addr + (kb ^ (((i >> 1) & 3) << 5)) + (i >> 3) * 4096 + (i & 1) * 2048; };
  auto vaddr = [&](int i) { return slot_addr + (vb ^ ((i & 3) << 5)) + ((i >> 2) & 1) * 4096 + (i >> 3) * 2048; };
  uint32_t a[4][4];
  float sv[2][4];
#pragma unroll
  for (int kg = 0; kg < 2; kg++)
#pragma unroll
    for (int i = 0; i < 4; i++) sv[kg][i] = 0.f;
#pragma unroll
  for (int i = 0; i < 4; i++) ldsm4(a[i], kaddr(i));
#pragma unroll
  for (int i = 0; i < 16; i++) {
    mma16816(sv[i & 1], a[i & 3][0], a[i & 3][1], a[i & 3][2], a[i & 3][3], qf[i >> 1][0], qf[i >> 1][1]);
    if (i + 4 < 16) ldsm4(a[i & 3], kaddr(i + 4));
  }
#pragma unroll
  for (int i = 0; i < 4; i++) ldsm4t(a[i], vaddr(i));
  float t0 = fmaxf(fmaxf(sv[0][0], sv[0][2]), fmaxf(sv[1][0], sv[1][2]));
  float t1 = fmaxf(fmaxf(sv[0][1], sv[0][3]), fmaxf(sv[1][1], sv[1][3]));
#pragma unroll
  for (int o = 4; o < 32; o <<= 1) {
    t0 = fmaxf(t0, __shfl_xor_sync(0xffffffffu, t0, o));
    t1 = fmaxf(t1, __shfl_xor_sync(0xffffffffu, t1, o));
  }
  if (__any_sync(0xffffffffu, (t0 > st.m0) || (t1 > st.m1))) {
    float n0 = fmaxf(st.m0, t0), n1 = fmaxf(st.m1, t1);
    float a0 = ex2((st.m0 - n0) * SCALE_LOG2), a1 = ex2((st.m1 - n1) * SCALE_LOG2);
    st.m0 = n0;
    st.m1 = n1;
    st.l0 *= a0;
    st.l1 *= a1;
#pragma unroll
    for (int mt = 0; mt < 8; mt++) {
      st.acc[mt][0] *= a0;
      st.acc[mt][1] *= a1;
      st.acc[mt][2] *= a0;
      st.acc[mt][3] *= a1;
    }
  }
  const float c0 = -st.m0 * SCALE_LOG2, c1 = -st.m1 * SCALE_LOG2;
  uint32_t pb[2][2];
#pragma unroll
  for (int kg = 0; kg < 2; kg++) {
    float p0 = ex2(fmaf(sv[kg][0], SCALE_LOG2, c0));
    float p1 = ex2(fmaf(sv[kg][1], SCALE_LOG2, c1));
    float p2 = ex2(fmaf(sv[kg][2], SCALE_LOG2, c0));
    float p3 = ex2(fmaf(sv[kg][3], SCALE_LOG2, c1));
    st.l0 += p0 + p2;
    st.l1 += p1 + p3;
    pb[kg][0] = movm(pack_bf16(p0, p1));
    pb[kg][1] = movm(pack_bf16(p2, p3));
  }
#pragma unroll
  for (int i = 0; i < 16; i++) {
    mma16816(st.acc[i & 7], a[i & 3][0], a[i & 3][1], a[i & 3][2], a[i & 3][3], pb[i >> 3][0], pb[i >> 3][1]);
    if (i + 4 < 16) ldsm4t(a[i & 3], vaddr(i + 4));
  }
}

template <int SLEEP>
__device__ __forceinline__ void fetch_q(uint32_t (&qf)[8][2], const float* q, int lane, uint32_t tag) {
  const float* qp = q + ((lane >> 2) & 3) * 128 + (lane >> 4) * 64 + (lane & 3) * 16;
  uint4 v[4];
  if (SLEEP)
    poll<4, SLEEP>(v, qp, 4, tag);
  else
    poll1<4>(v, qp, 4, tag);
  __syncwarp();
#pragma unroll
  for (int u = 0; u < 4; u++) {
    uint32_t r0 = __byte_perm(v[u].x, v[u].y, 0x7632);
    uint32_t r1 = __byte_perm(v[u].z, v[u].w, 0x7632);
    uint32_t o0 = __shfl_down_sync(0xffffffffu, r0, 16);
    uint32_t o1 = __shfl_down_sync(0xffffffffu, r1, 16);
    bool lo = lane < 16;
    qf[u][0] = lo ? r0 : 0u;
    qf[u][1] = lo ? r1 : 0u;
    qf[4 + u][0] = lo ? o0 : 0u;
    qf[4 + u][1] = lo ? o1 : 0u;
  }
}

template <int LAYER, int NW>
__device__ __forceinline__ void attn_role(char* smem, int w_, int lane_, int cta_, uint32_t ep1, uint32_t koff) {
  const int w = w_, lane = lane_;
  const uint32_t tag = ep1 & 1;
  const uint32_t sbase = smem_u32(smem);
  const uint32_t bars = sbase + OFF_BAR;
  const uint32_t state = sbase + OFF_MISC;
  const uint32_t info = sbase + OFF_INFO, linfo = info + NB * NT;
  float* mbuf = (float*)(smem + (LAYER ? OFF_MB2 : OFF_MB1));
  float* mlbuf = (float*)(smem + (LAYER ? OFF_ML2 : OFF_ML1));
  const uint32_t x7 = lane & 7;
  const uint32_t kb = (x7 + 8 * ((lane >> 3) & 1)) * 128 + ((((uint32_t)lane >> 4) ^ x7) << 4) + koff;
  const uint32_t vb = (x7 + 8 * (lane >> 4)) * 128 + (((((uint32_t)lane >> 3) & 1) ^ x7) << 4) + (koff ^ HALF_BYTES);
  uint32_t lpar = 0;

#pragma unroll 1
  for (int b = 0; b < NB; b++) {
    uint32_t qf[8][2];
    {
      const int lane = opq(lane_), cta = opq(cta_);
      if (LAYER == 1) mbar_wait(bars + 8 * (BAR_QGO + b), 0);
      if (w == 0 && lane == 0) TL(1 + LAYER, b * 8 + 0);
      if (LAYER == 1 || b == 0) {
        fetch_q<LAYER ? 50 : 100>(qf, &g_q[LAYER][b][cta >> 4][0], lane, tag);
        if (lane == 0) mbar_arrive(bars + 8 * (LAYER == 0 ? BAR_Q1 : BAR_LGO + b));
      } else {
        const uint4* qs = (const uint4*)(smem + OFF_QS + (b & 1) * 1024 + (lane & 15) * 64);
#pragma unroll
        for (int u = 0; u < 4; u++) {
          uint4 t = lane < 16 ? qs[u] : make_uint4(0u, 0u, 0u, 0u);
          qf[2 * u][0] = t.x;
          qf[2 * u][1] = t.y;
          qf[2 * u + 1][0] = t.z;
          qf[2 * u + 1][1] = t.w;
        }
      }
    }
    if (w == 0 && lane == 0) TL(1 + LAYER, b * 8 + 1);
    AttnState st;
#pragma unroll
    for (int mt = 0; mt < 8; mt++)
#pragma unroll
      for (int i = 0; i < 4; i++) st.acc[mt][i] = 0.f;
    st.m0 = st.m1 = -INFINITY;
    st.l0 = st.l1 = 0.f;

    if (LAYER == 0) {
#pragma unroll 1
      for (int t = w; t < NT; t += NW) {
        const uint32_t fb = bars + 8 * (BAR_FULLD + ((b & 1) * NT + t) * 2);
        mbar_wait(fb, (b >> 1) & 1);
        mbar_wait(fb + 8, (b >> 1) & 1);
        uint32_t inf = lds8(info + b * NT + t);
        uint32_t slot = inf & 0x3f;
        process_tile(sbase + slot * TILE_BYTES, kb, vb, qf, st);
        __syncwarp();
        if (!(inf & 0x80) && lane == 0) state_add(state, 1u << slot);
        if (t == 8 && b + 1 < NB) {
          const int ln = opq(lane_);
          const float* qp = &g_q[0][b + 1][opq(cta_) >> 4][((ln >> 2) & 3) * 128 + (ln >> 4) * 64 + (ln & 3) * 16];
          uint4 v[4];
          poll<4, 100>(v, qp, 4, tag);
          uint4* qs = (uint4*)(smem + OFF_QS + ((b + 1) & 1) * 1024 + (ln & 15) * 64 + (ln >> 4) * 32);
          qs[0] = make_uint4(__byte_perm(v[0].x, v[0].y, 0x7632), __byte_perm(v[0].z, v[0].w, 0x7632),
                             __byte_perm(v[1].x, v[1].y, 0x7632), __byte_perm(v[1].z, v[1].w, 0x7632));
          qs[1] = make_uint4(__byte_perm(v[2].x, v[2].y, 0x7632), __byte_perm(v[2].z, v[2].w, 0x7632),
                             __byte_perm(v[3].x, v[3].y, 0x7632), __byte_perm(v[3].z, v[3].w, 0x7632));
          __syncwarp();
        }
      }
    } else {
#pragma unroll 1
      for (int i = 0; i < 2 * (NT / NW); i++) {
        int t = w + NW * (i % (NT / NW));
        uint32_t inf = lds8(info + b * NT + t);
        bool ret = inf & 0x80;
        if (ret != (i < NT / NW)) continue;
        uint32_t slot = inf & 0x3f;
        if (!ret) {
          int bi = (b & 1) * NT + t;
          mbar_wait(bars + 8 * (BAR_FULLL + 2 * bi), (lpar >> bi) & 1);
          mbar_wait(bars + 8 * (BAR_FULLL + 2 * bi + 1), (lpar >> bi) & 1);
          lpar ^= 1u << bi;
          slot = lds8(linfo + b * NT + t);
        }
        process_tile(sbase + slot * TILE_BYTES, kb, vb, qf, st);
        __syncwarp();
        if (lane == 0) state_add(state, (1u << slot) + ST_DONE - (ret ? ST_RET : 0u));
      }
    }

    if (lane == 0) TL(1 + LAYER, b * 8 + 2 + (w & 1));
    {
    const int lane = opq(lane_), w = opq(w_), cta = opq(cta_), g8 = lane >> 2, j = lane & 3;
    constexpr int OWN = 8 / NW;
#pragma unroll
    for (int o = 4; o < 32; o <<= 1) {
      st.l0 += __shfl_xor_sync(0xffffffffu, st.l0, o);
      st.l1 += __shfl_xor_sync(0xffffffffu, st.l1, o);
    }
    if (lane < 2) *(float4*)&mlbuf[w * 8 + lane * 4] = make_float4(st.m0, st.l0, st.m1, st.l1);
    if (j < 2) {
#pragma unroll
      for (int mt = 0; mt < 8; mt++) {
        int ow = mt / OWN;
        if (ow != w) {
          int sr = (w - ow - 1) & (NW - 1);
          *(float4*)&mbuf[(((ow * (NW - 1) + sr) * OWN + (mt % OWN)) * 16 + g8 * 2 + j) * 4] =
              make_float4(st.acc[mt][0], st.acc[mt][1], st.acc[mt][2], st.acc[mt][3]);
        }
      }
    }
    bar_sync(2 + LAYER, 32 * NW);
    if (j < 2) {
      float4 mlv[NW];
#pragma unroll
      for (int u = 0; u < NW; u++) mlv[u] = *(const float4*)&mlbuf[((w + u) & (NW - 1)) * 8 + j * 4];
      float M0 = mlv[0].x, M1 = mlv[0].z;
#pragma unroll
      for (int u = 1; u < NW; u++) {
        M0 = fmaxf(M0, mlv[u].x);
        M1 = fmaxf(M1, mlv[u].z);
      }
      float f0[NW], f1[NW], L0 = 0.f, L1 = 0.f;
#pragma unroll
      for (int u = 0; u < NW; u++) {
        f0[u] = ex2((mlv[u].x - M0) * SCALE_LOG2);
        f1[u] = ex2((mlv[u].z - M1) * SCALE_LOG2);
        L0 = fmaf(f0[u], mlv[u].y, L0);
        L1 = fmaf(f1[u], mlv[u].w, L1);
      }
      float* pp = &g_part[LAYER][b][cta][0];
#pragma unroll
      for (int e2 = 0; e2 < OWN / 2; e2++) {
        float o[2][4];
#pragma unroll
        for (int e1 = 0; e1 < 2; e1++) {
          const int e = 2 * e2 + e1;
          float o0 = 0.f, o1 = 0.f, o2 = 0.f, o3 = 0.f;
#pragma unroll
          for (int cw = 0; cw < NW; cw++) {
            sel_if(o0, st.acc[OWN * cw + e][0], w, cw);
            sel_if(o1, st.acc[OWN * cw + e][1], w, cw);
            sel_if(o2, st.acc[OWN * cw + e][2], w, cw);
            sel_if(o3, st.acc[OWN * cw + e][3], w, cw);
          }
          o0 *= f0[0];
          o1 *= f1[0];
          o2 *= f0[0];
          o3 *= f1[0];
#pragma unroll
          for (int sr = 0; sr < NW - 1; sr++) {
            float4 a = *(const float4*)&mbuf[(((w * (NW - 1) + sr) * OWN + e) * 16 + g8 * 2 + j) * 4];
            o0 = fmaf(a.x, f0[sr + 1], o0);
            o1 = fmaf(a.y, f1[sr + 1], o1);
            o2 = fmaf(a.z, f0[sr + 1], o2);
            o3 = fmaf(a.w, f1[sr + 1], o3);
          }
          o[e1][0] = o0;
          o[e1][1] = o1;
          o[e1][2] = o2;
          o[e1][3] = o3;
        }
        const int u = (OWN / 2) * w + e2;
        st_rlx_bf4(pp + (2 * j) * 64 + u * 16 + 2 * g8, o[0][0], o[0][2], o[1][0], o[1][2], tag);
        st_rlx_bf4(pp + (2 * j + 1) * 64 + u * 16 + 2 * g8, o[0][1], o[0][3], o[1][1], o[1][3], tag);
      }
      if (w == 0 && g8 == 0) st_rlx4(pp + 256 + 4 * j, M0, L0, M1, L1, tag);
    }
    __syncwarp();
    if (w == 0 && lane == 0) TL(1 + LAYER, b * 8 + 4);
    if (lane == 0) mbar_arrive_relaxed(bars + 8 * ((LAYER ? BAR_P2DONE : BAR_P1DONE) + b));
    bar_sync(2 + LAYER, 32 * NW);
    }
  }
}

constexpr uint32_t ONES2 = 0x3F803F80u;

template <int SLEEP>
__device__ __forceinline__ void attn_out(const float* part  , int g, int w, int lane, uint32_t tag,
                                         const uint32_t (&wa)[4][4][4], float* red) {
  const int g8 = lane >> 2, j = lane & 3;
  const float* base = part + (size_t)(16 * g + g8) * PART_STRIDE;
  const float* po = base + 32 * w + 4 * j;
  const float* pm = base + 256 + 2 * (w >> 1);
  uint2 ml0 = ld_rlx2(pm), ml1 = ld_rlx2(pm + 8 * PART_STRIDE);
  uint4 o4[2][2];
#pragma unroll
  for (int sg = 0; sg < 2; sg++)
#pragma unroll
    for (int u = 0; u < 2; u++) o4[sg][u] = ld_rlx4(po + sg * 8 * PART_STRIDE + 16 * u);
  uint32_t it = 0;
  while (true) {
    const uint32_t bad0 = (ml0.x ^ tag) | bad4(o4[0][0], tag) | bad4(o4[0][1], tag);
    const uint32_t bad1 = (ml1.x ^ tag) | bad4(o4[1][0], tag) | bad4(o4[1][1], tag);
    if (!((bad0 | bad1) & 1)) break;
    if (SLEEP) __nanosleep(SLEEP);
    if (bad0 & 1) {
      ml0 = ld_rlx2(pm);
      o4[0][0] = ld_rlx4(po);
      o4[0][1] = ld_rlx4(po + 16);
    }
    if (bad1 & 1) {
      ml1 = ld_rlx2(pm + 8 * PART_STRIDE);
      o4[1][0] = ld_rlx4(po + 8 * PART_STRIDE);
      o4[1][1] = ld_rlx4(po + 8 * PART_STRIDE + 16);
    }
    if (++it > SPIN_LIMIT) __trap();
  }
  __syncwarp();
  float M = fmaxf(u2f(ml0.x), u2f(ml1.x));
#pragma unroll
  for (int o = 4; o < 32; o <<= 1) M = fmaxf(M, __shfl_xor_sync(0xffffffffu, M, o));
  float fo0 = ex2((u2f(ml0.x) - M) * SCALE_LOG2), fo1 = ex2((u2f(ml1.x) - M) * SCALE_LOG2);
  float L = fmaf(fo0, u2f(ml0.y), fo1 * u2f(ml1.y));
#pragma unroll
  for (int o = 4; o < 32; o <<= 1) L += __shfl_xor_sync(0xffffffffu, L, o);
  const float inv = rcp_fast(L);
  fo0 *= inv;
  fo1 *= inv;
  float y[8];
#pragma unroll
  for (int sg = 0; sg < 2; sg++) {
    float acc[4][4];
#pragma unroll
    for (int mt = 0; mt < 4; mt++)
#pragma unroll
      for (int i = 0; i < 4; i++) acc[mt][i] = 0.f;
#pragma unroll
    for (int ks = 0; ks < 4; ks++) {
      const uint32_t b0 = (ks & 1) ? o4[sg][ks >> 1].z : o4[sg][ks >> 1].x;
      const uint32_t b1 = (ks & 1) ? o4[sg][ks >> 1].w : o4[sg][ks >> 1].y;
#pragma unroll
      for (int mt = 0; mt < 4; mt++) mma16816(acc[mt], wa[ks][mt][0], wa[ks][mt][1], wa[ks][mt][2], wa[ks][mt][3], b0, b1);
    }
    const float f0 = __shfl_sync(0xffffffffu, sg ? fo1 : fo0, 8 * j);
    const float f1 = __shfl_sync(0xffffffffu, sg ? fo1 : fo0, 8 * j + 4);
#pragma unroll
    for (int mt = 0; mt < 4; mt++)
#pragma unroll
      for (int hf = 0; hf < 2; hf++) {
        const float t = fmaf(f0, acc[mt][2 * hf], f1 * acc[mt][2 * hf + 1]);
        y[2 * mt + hf] = sg ? y[2 * mt + hf] + t : t;
      }
  }
#pragma unroll
  for (int o = 1; o < 4; o <<= 1) {
#pragma unroll
    for (int i = 0; i < 8; i++) y[i] += __shfl_xor_sync(0xffffffffu, y[i], o);
  }
  if (j == 0) {
    *(float4*)&red[8 * g8] = make_float4(y[0], y[1], y[2], y[3]);
    *(float4*)&red[8 * g8 + 4] = make_float4(y[4], y[5], y[6], y[7]);
  }
}

__device__ __forceinline__ int q_lpos(int c) {
  int kk = c >> 4, r = c & 15;
  return ((r & 7) >> 1) * 16 + kk * 4 + (r & 1) + 2 * (r >> 3);
}

__device__ __forceinline__ float4 sum8(const float* p, int stride) {
  float4 a = *(const float4*)p;
#pragma unroll
  for (int u = 1; u < 8; u++) {
    float4 t = *(const float4*)(p + u * stride);
    a.x += t.x;
    a.y += t.y;
    a.z += t.z;
    a.w += t.w;
  }
  return a;
}

#define CHAIN_IDS                                                                                             \
  const int tid = opq(tid_), cta = opq(cta_);                                                                 \
  const int w = tid >> 5, lane = tid & 31, g8 = lane >> 2, j = lane & 3;                                      \
  const int g = cta >> 4, hb = (cta & 15) >> 1, i64 = g * 8 + hb, cb = i64 & 15, kq = i64 >> 4;               \
  const int n = tid >> 7, quad = tid & 127;                                                                   \
  const uint32_t ones_row = g8 == 0 ? ONES2 : 0u;                                                             \
  (void)w, (void)lane, (void)g8, (void)j, (void)g, (void)hb, (void)i64, (void)cb, (void)kq, (void)n, (void)quad, \
      (void)ones_row;

template <typename F>
__device__ __forceinline__ void load_wa(uint32_t (&wa)[4][4][4], const __nv_bfloat16* base, int pitch, F rowf) {
#pragma unroll
  for (int ks = 0; ks < 4; ks++) {
    uint4 r[4];
#pragma unroll
    for (int e = 0; e < 4; e++) r[e] = __ldg((const uint4*)(base + (size_t)rowf(ks, e) * pitch));
    const uint32_t c0[4] = {r[0].x, r[0].y, r[0].z, r[0].w}, c1[4] = {r[1].x, r[1].y, r[1].z, r[1].w};
    const uint32_t c2[4] = {r[2].x, r[2].y, r[2].z, r[2].w}, c3[4] = {r[3].x, r[3].y, r[3].z, r[3].w};
#pragma unroll
    for (int mt = 0; mt < 4; mt++) {
      wa[ks][mt][0] = __byte_perm(c0[mt], c1[mt], 0x5410);
      wa[ks][mt][1] = __byte_perm(c0[mt], c1[mt], 0x7632);
      wa[ks][mt][2] = __byte_perm(c2[mt], c3[mt], 0x5410);
      wa[ks][mt][3] = __byte_perm(c2[mt], c3[mt], 0x7632);
    }
  }
}

__device__ __forceinline__ void chain_role(char* smem, int tid_, int cta_, uint32_t ep1, const __nv_bfloat16* __restrict__ x,
                                           const __nv_bfloat16* __restrict__ wq, const __nv_bfloat16* __restrict__ wo,
                                           const __nv_bfloat16* __restrict__ w1, const __nv_bfloat16* __restrict__ w2,
                                           __nv_bfloat16* __restrict__ out) {
  const uint32_t sbase = smem_u32(smem);
  const uint32_t bars = sbase + OFF_BAR;
  const uint32_t tag = ep1 & 1;
  const bool set1 = cta_ & 1;
  __nv_bfloat16* xs = (__nv_bfloat16*)(smem + OFF_XS);
  float* redA = (float*)(smem + OFF_REDA);
  float* redC = (float*)(smem + OFF_REDC);
  float* red1 = (float*)(smem + OFF_RED1);
  float* stat = (float*)(smem + OFF_STAT);
  float* csum = (float*)(smem + OFF_CSUM);

  uint32_t wa[4][4][4];
  uint32_t wb[4][2][4];

  if (set1) {
    {
      CHAIN_IDS
      const uint4* xp = (const uint4*)x;
      uint4 x0 = __ldg(xp + tid), x1 = __ldg(xp + tid + 256);
      load_wa(wa, wq + 512 * g + 64 * hb + 8 * g8, 4096, [&](int ks, int e) { return 64 * w + 16 * ks + 4 * j + e; });
      uint4* xn = (uint4*)(smem + OFF_MB1);
      xn[tid] = x0;
      xn[tid + 256] = x1;
    }
    bar_sync(1, 256);
    {
      CHAIN_IDS
      float c[4][4], cs[4][4], sa[4] = {0.f, 0.f, 0.f, 0.f};
#pragma unroll
      for (int mt = 0; mt < 4; mt++)
#pragma unroll
        for (int i = 0; i < 4; i++) c[mt][i] = cs[mt][i] = 0.f;
#pragma unroll
      for (int ks = 0; ks < 4; ks++) {
        uint2 bv = *(const uint2*)(smem + OFF_MB1 + (g8 * 512 + 64 * w + 16 * ks + 4 * j) * 2);
#pragma unroll
        for (int mt = 0; mt < 4; mt++) {
          mma16816(c[mt], wa[ks][mt][0], wa[ks][mt][1], wa[ks][mt][2], wa[ks][mt][3], bv.x, bv.y);
          mma16816(cs[mt], wa[ks][mt][0], wa[ks][mt][1], wa[ks][mt][2], wa[ks][mt][3], ONES2, ONES2);
        }
        mma16816(sa, bv.x, ones_row, bv.y, ones_row, bv.x, bv.y);
      }
      float* st16 = (float*)(smem + OFF_XS);
      if (j == 0) {
#pragma unroll
        for (int mt = 0; mt < 4; mt++)
#pragma unroll
          for (int hf = 0; hf < 2; hf++) red1[w * 64 + q_lpos(8 * g8 + 2 * mt + hf)] = cs[mt][2 * hf];
      }
      if (j == (g8 >> 1)) st16[w * 16 + g8] = (g8 & 1) ? sa[1] : sa[0];
      if (g8 == 0) {
        st16[w * 16 + 8 + 2 * j] = sa[2];
        st16[w * 16 + 8 + 2 * j + 1] = sa[3];
      }
      float* rb = (float*)(smem + OFF_MB1);
#pragma unroll
      for (int rnd = 0; rnd < 2; rnd++) {
        bar_sync(1, 256);
        if ((j >> 1) == rnd) {
#pragma unroll
          for (int mt = 0; mt < 4; mt++)
#pragma unroll
            for (int hf = 0; hf < 2; hf++) {
              const int lp = q_lpos(8 * g8 + 2 * mt + hf);
              rb[(w * 4 + 2 * (j & 1)) * 64 + lp] = c[mt][2 * hf];
              rb[(w * 4 + 2 * (j & 1) + 1) * 64 + lp] = c[mt][2 * hf + 1];
            }
        }
        bar_sync(1, 256);
        if (tid < 64) {
          const int nl = tid >> 4, qd = tid & 15, nb = 4 * rnd + nl;
          float4 a = sum8(rb + nl * 64 + 4 * qd, 256);
          float4 cs4 = sum8(red1 + 4 * qd, 64);
          float sxx = 0.f, sx = 0.f;
#pragma unroll
          for (int u = 0; u < 8; u++) {
            sxx += st16[u * 16 + nb];
            sx += st16[u * 16 + 8 + nb];
          }
          float mb, rden;
          ln_consts(sx, sxx, mb, rden);
          st_rlx4(&g_q[0][nb][g][64 * hb + 4 * qd], rbf((a.x - mb * cs4.x) * rden), rbf((a.y - mb * cs4.y) * rden),
                  rbf((a.z - mb * cs4.z) * rden), rbf((a.w - mb * cs4.w) * rden), tag);
          if (nb == 0) *(float4*)&csum[4 * qd] = cs4;
        }
      }
      if (tid == 0) TL(0, 200);
    }
  }
  mbar_wait(bars + 8 * BAR_Q1, 0);
  {
    CHAIN_IDS
    if (!set1)
      load_wa(wa, wo + (size_t)512 * g * 512 + 64 * hb + 8 * g8, 512, [&](int ks, int e) {
        const int p = 64 * w + 32 * (ks >> 1) + 8 * j + 4 * (ks & 1) + e;
        const int pp = p & 127;
        return (p & ~127) + (pp >> 5) * 32 + ((pp >> 1) & 1) * 16 + ((pp & 31) >> 2) + 8 * (pp & 1);
      });
    const __nv_bfloat16* bp = set1 ? w1 + 32 * i64 + 4 * g8 : w2 + (size_t)448 * kq * 512 + 32 * cb + 4 * g8;
    const int pitch = set1 ? 1792 : 512;
    const bool valid = set1 ? i64 < 56 : w < 7;
    uint2 r[4][4];
#pragma unroll
    for (int ks = 0; ks < 4; ks++)
#pragma unroll
      for (int e = 0; e < 4; e++)
        r[ks][e] = valid ? __ldg((const uint2*)(bp + (size_t)(64 * w + 16 * ks + 4 * j + e) * pitch)) : make_uint2(0u, 0u);
#pragma unroll
    for (int ks = 0; ks < 4; ks++) {
      wb[ks][0][0] = __byte_perm(r[ks][0].x, r[ks][1].x, 0x5410);
      wb[ks][0][1] = __byte_perm(r[ks][0].x, r[ks][1].x, 0x7632);
      wb[ks][0][2] = __byte_perm(r[ks][2].x, r[ks][3].x, 0x5410);
      wb[ks][0][3] = __byte_perm(r[ks][2].x, r[ks][3].x, 0x7632);
      wb[ks][1][0] = __byte_perm(r[ks][0].y, r[ks][1].y, 0x5410);
      wb[ks][1][1] = __byte_perm(r[ks][0].y, r[ks][1].y, 0x7632);
      wb[ks][1][2] = __byte_perm(r[ks][2].y, r[ks][3].y, 0x5410);
      wb[ks][1][3] = __byte_perm(r[ks][2].y, r[ks][3].y, 0x7632);
    }
    bar_sync(1, 256);
    if (set1) {
      float cs[2][4] = {{0.f, 0.f, 0.f, 0.f}, {0.f, 0.f, 0.f, 0.f}};
#pragma unroll
      for (int ks = 0; ks < 4; ks++) {
        mma16816(cs[0], wb[ks][0][0], wb[ks][0][1], wb[ks][0][2], wb[ks][0][3], ONES2, ONES2);
        mma16816(cs[1], wb[ks][1][0], wb[ks][1][1], wb[ks][1][2], wb[ks][1][3], ONES2, ONES2);
      }
      if (j == 0) *(float4*)&red1[w * 32 + 4 * g8] = make_float4(cs[0][0], cs[0][2], cs[1][0], cs[1][2]);
      *(uint2*)(xs + 512 + 4 * tid) = make_uint2(0u, 0u);
    } else {
      if (tid < 128) *(float4*)&redA[(tid >> 4) * 128 + 64 + 4 * (tid & 15)] = make_float4(0.f, 0.f, 0.f, 0.f);
    }
    bar_sync(1, 256);
    if (set1 && tid < 8) *(float4*)&csum[64 + 4 * tid] = sum8(red1 + 4 * tid, 32);
    if (tid == 0) TL(0, 201);
  }

#pragma unroll 1
  for (int c = 0; c <= NB; c++) {
    const bool has_mid = c < NB, has_post = c >= 2;
    if (!set1) {
      {
        CHAIN_IDS
        if (has_post) {
          mbar_wait(bars + 8 * (BAR_P2DONE + c - 2), 0);
          if (tid == 0) TLX(0, c * 16 + 0);
          attn_out<300>(&g_part[1][c - 2][0][0], g, w, lane, tag, wa, redA + w * 128 + (has_mid ? 64 : 0));
          if (tid == 0) TLX(0, c * 16 + 1);
        }
        mbar_wait(bars + 8 * (has_mid ? BAR_P1DONE + c : BAR_P2DONE + NB - 1), 0);
        if (tid == 0) TL(0, c * 16 + 2);
        attn_out<PS>(has_mid ? &g_part[0][c][0][0] : &g_part[1][NB - 1][0][0], g, w, lane, tag, wa,
                     redA + w * 128 + (has_mid ? 0 : 64));
        if (tid == 0) TLX(0, c * 16 + 3);
        bar_sync(1, 256);
        if (tid < 32) {
          float4 a = sum8(redA + 4 * tid, 128);
          st_rlx_bf4(&g_y[c][tid >> 4][g][32 * hb + 2 * (tid & 15)], a.x, a.y, a.z, a.w, tag);
        }
        if (tid == 0) TLX(0, c * 16 + 4);
      }
      {
        CHAIN_IDS
        float acc[2][4] = {{0.f, 0.f, 0.f, 0.f}, {0.f, 0.f, 0.f, 0.f}};
        if (w < 7) {
          const float* hp = &g_h[c][g8 & 1][448 * kq + 64 * w + 4 * j];
          uint4 v[4];
          if (g8 < 2) {
            poll1<4>(v, hp, 16, tag);
          } else {
#pragma unroll
            for (int u = 0; u < 4; u++) v[u] = make_uint4(0u, 0u, 0u, 0u);
          }
          __syncwarp();
          if (tid == 0) TLX(0, c * 16 + 7);
#pragma unroll
          for (int ks = 0; ks < 4; ks++) {
            const uint32_t b0 = __byte_perm(v[ks].x, v[ks].y, 0x7632), b1 = __byte_perm(v[ks].z, v[ks].w, 0x7632);
            mma16816(acc[0], wb[ks][0][0], wb[ks][0][1], wb[ks][0][2], wb[ks][0][3], b0, b1);
            mma16816(acc[1], wb[ks][1][0], wb[ks][1][1], wb[ks][1][2], wb[ks][1][3], b0, b1);
          }
        }
        if (j == 0) {
          *(float4*)&redC[w * 64 + 4 * g8] = make_float4(acc[0][0], acc[0][2], acc[1][0], acc[1][2]);
          *(float4*)&redC[w * 64 + 32 + 4 * g8] = make_float4(acc[0][1], acc[0][3], acc[1][1], acc[1][3]);
        }
        bar_sync(1, 256);
        if (tid == 32 && has_mid) mbar_arrive_relaxed(bars + 8 * (BAR_QGO + c));
        if (tid < 16) {
          float4 a = sum8(redC + 4 * tid, 64);
          st_rlx4(&g_z[c][tid >> 3][kq][32 * cb + 4 * (tid & 7)], a.x, a.y, a.z, a.w, tag);
        }
        if (tid == 0) TLX(0, c * 16 + 8);
      }
    } else {
      const int b0i = has_mid ? c : NB - 2, b1i = has_mid ? c + 1 : NB - 1;
      __nv_bfloat16* xmid = xs + (b0i % 3) * 512;
      __nv_bfloat16* xpost = xs + (b1i % 3) * 512;
      uint2 bs;
      {
        CHAIN_IDS
        if (n == 0 && has_mid)
          bs = __ldg((const uint2*)(x + c * 512 + 4 * quad));
        else
          bs = *(const uint2*)((n ? xpost : xmid) + 4 * quad);
        mbar_wait(bars + 8 * (has_mid ? BAR_P1DONE + c : BAR_P2DONE + NB - 1), 0);
        if (tid == 0) TL(0, c * 16 + 2);
        const float* yp = &g_y[c][n][0][2 * quad];
        uint2 v[8];
        pollS<8, PS>(v, yp, 256, tag);
        if (tid == 0) TLX(0, c * 16 + 5);
        float a0 = ((bf_lo(v[0].x) + bf_lo(v[1].x)) + (bf_lo(v[2].x) + bf_lo(v[3].x))) + ((bf_lo(v[4].x) + bf_lo(v[5].x)) + (bf_lo(v[6].x) + bf_lo(v[7].x)));
        float a1 = ((bf_hi(v[0].x) + bf_hi(v[1].x)) + (bf_hi(v[2].x) + bf_hi(v[3].x))) + ((bf_hi(v[4].x) + bf_hi(v[5].x)) + (bf_hi(v[6].x) + bf_hi(v[7].x)));
        float a2 = ((bf_lo(v[0].y) + bf_lo(v[1].y)) + (bf_lo(v[2].y) + bf_lo(v[3].y))) + ((bf_lo(v[4].y) + bf_lo(v[5].y)) + (bf_lo(v[6].y) + bf_lo(v[7].y)));
        float a3 = ((bf_hi(v[0].y) + bf_hi(v[1].y)) + (bf_hi(v[2].y) + bf_hi(v[3].y))) + ((bf_hi(v[4].y) + bf_hi(v[5].y)) + (bf_hi(v[6].y) + bf_hi(v[7].y)));
        uint32_t p0 = pack_bf16(a0, a1), p1 = pack_bf16(a2, a3);
        p0 = pack_bf16(bf_lo(bs.x) + bf_lo(p0), bf_hi(bs.x) + bf_hi(p0));
        p1 = pack_bf16(bf_lo(bs.y) + bf_lo(p1), bf_hi(bs.y) + bf_hi(p1));
        bs = make_uint2(p0, p1);
        *(uint2*)((n ? xpost : xmid) + 4 * quad) = bs;
        bar_sync(1, 256);
        const __nv_bfloat16* xv = ((g8 & 1) ? xpost : xmid) + 64 * w + 4 * j;
        float acc[2][4] = {{0.f, 0.f, 0.f, 0.f}, {0.f, 0.f, 0.f, 0.f}}, sa[4] = {0.f, 0.f, 0.f, 0.f};
#pragma unroll
        for (int ks = 0; ks < 4; ks++) {
          uint2 t = *(const uint2*)(xv + 16 * ks);
          mma16816(acc[0], wb[ks][0][0], wb[ks][0][1], wb[ks][0][2], wb[ks][0][3], t.x, t.y);
          mma16816(acc[1], wb[ks][1][0], wb[ks][1][1], wb[ks][1][2], wb[ks][1][3], t.x, t.y);
          mma16816(sa, t.x, ones_row, t.y, ones_row, t.x, t.y);
        }
        if (j == 0) {
          *(float4*)&red1[w * 64 + 4 * g8] = make_float4(acc[0][0], acc[0][2], acc[1][0], acc[1][2]);
          *(float4*)&red1[w * 64 + 32 + 4 * g8] = make_float4(acc[0][1], acc[0][3], acc[1][1], acc[1][3]);
          if (g8 == 0) {
            stat[w * 4 + 0] = sa[0];
            stat[w * 4 + 1] = sa[2];
            stat[w * 4 + 3] = sa[3];
          }
          if (g8 == 1) stat[w * 4 + 2] = sa[1];
        }
        bar_sync(1, 256);
        if (w == 0 && i64 < 56) {
          float4 a = sum8(lane < 16 ? red1 + 4 * lane : stat, lane < 16 ? 64 : 4);
          float4 cs4 = *(const float4*)&csum[64 + 4 * (lane & 7)];
          float mb, rden;
          ln_consts(lane & 1 ? a.w : a.y, lane & 1 ? a.z : a.x, mb, rden);
          mb = __shfl_sync(0xffffffffu, mb, 16 + ((lane >> 3) & 1));
          rden = __shfl_sync(0xffffffffu, rden, 16 + ((lane >> 3) & 1));
          float h0 = rbf((a.x - mb * cs4.x) * rden), h1 = rbf((a.y - mb * cs4.y) * rden);
          float h2 = rbf((a.z - mb * cs4.z) * rden), h3 = rbf((a.w - mb * cs4.w) * rden);
          h0 = rbf(h0 * rcp_fast(1.f + ex2(-1.4426950408889634f * h0)));
          h1 = rbf(h1 * rcp_fast(1.f + ex2(-1.4426950408889634f * h1)));
          h2 = rbf(h2 * rcp_fast(1.f + ex2(-1.4426950408889634f * h2)));
          h3 = rbf(h3 * rcp_fast(1.f + ex2(-1.4426950408889634f * h3)));
          if (lane < 16) st_rlx4(&g_h[c][lane >> 3][32 * i64 + 4 * (lane & 7)], h0, h1, h2, h3, tag);
        }
        if (tid == 0) TLX(0, c * 16 + 6);
      }
      {
        CHAIN_IDS
        const bool active = (n == 0 && has_mid) || (has_post && (quad >> 1) == i64);
        if (active) {
          const float* zp = &g_z[c][n][0][4 * quad];
          uint4 v[4];
          poll1<4>(v, zp, 512, tag);
          float a0 = (u2f(v[0].x) + u2f(v[1].x)) + (u2f(v[2].x) + u2f(v[3].x));
          float a1 = (u2f(v[0].y) + u2f(v[1].y)) + (u2f(v[2].y) + u2f(v[3].y));
          float a2 = (u2f(v[0].z) + u2f(v[1].z)) + (u2f(v[2].z) + u2f(v[3].z));
          float a3 = (u2f(v[0].w) + u2f(v[1].w)) + (u2f(v[2].w) + u2f(v[3].w));
          uint32_t p0 = pack_bf16(a0, a1), p1 = pack_bf16(a2, a3);
          p0 = pack_bf16(bf_lo(bs.x) + bf_lo(p0), bf_hi(bs.x) + bf_hi(p0));
          p1 = pack_bf16(bf_lo(bs.y) + bf_lo(p1), bf_hi(bs.y) + bf_hi(p1));
          if (n == 0 && has_mid)
            *(uint2*)(xmid + 4 * quad) = make_uint2(p0, p1);
          else
            *(uint2*)(out + (has_mid ? c - 2 : NB - 2 + n) * 512 + 4 * quad) = make_uint2(p0, p1);
        }
        __syncwarp();
        if (tid == 0) TLX(0, c * 16 + 9);
        if (!has_mid) break;
        bar_sync(1, 256);
        const __nv_bfloat16* xv = xmid + 64 * w + 4 * j;
        float acc[4][4], sa[4] = {0.f, 0.f, 0.f, 0.f};
#pragma unroll
        for (int mt = 0; mt < 4; mt++)
#pragma unroll
          for (int i = 0; i < 4; i++) acc[mt][i] = 0.f;
#pragma unroll
        for (int ks = 0; ks < 4; ks++) {
          uint2 t = *(const uint2*)(xv + 16 * ks);
#pragma unroll
          for (int mt = 0; mt < 4; mt++) mma16816(acc[mt], wa[ks][mt][0], wa[ks][mt][1], wa[ks][mt][2], wa[ks][mt][3], t.x, t.y);
          mma16816(sa, t.x, ones_row, t.y, ones_row, t.x, t.y);
        }
        if (j == 0) {
#pragma unroll
          for (int mt = 0; mt < 4; mt++)
#pragma unroll
            for (int hf = 0; hf < 2; hf++) red1[w * 64 + q_lpos(8 * g8 + 2 * mt + hf)] = acc[mt][2 * hf];
          if (g8 == 0) *(float2*)&stat[w * 4] = make_float2(sa[0], sa[2]);
        }
        bar_sync(1, 256);
        if (w == 0) {
          float4 a = sum8(lane < 16 ? red1 + 4 * lane : stat, lane < 16 ? 64 : 4);
          float4 cs4 = *(const float4*)&csum[4 * (lane & 15)];
          float mb, rden;
          ln_consts(a.y, a.x, mb, rden);
          mb = __shfl_sync(0xffffffffu, mb, 16);
          rden = __shfl_sync(0xffffffffu, rden, 16);
          if (lane < 16)
            st_rlx4(&g_q[1][c][g][64 * hb + 4 * lane], rbf((a.x - mb * cs4.x) * rden), rbf((a.y - mb * cs4.y) * rden),
                    rbf((a.z - mb * cs4.z) * rden), rbf((a.w - mb * cs4.w) * rden), tag);
          if (tid == 0) TL(0, c * 16 + 10);
          if (tid == 0) mbar_arrive_relaxed(bars + 8 * (BAR_QGO + c));
        }
      }
    }
  }
}

__device__ __forceinline__ void producer_d(char* smem, int cta, const CUtensorMap* tm) {
  const uint32_t sbase = smem_u32(smem);
  const uint32_t bars = sbase + OFF_BAR;
  const uint32_t state = sbase + OFF_MISC;
  const uint32_t info = sbase + OFF_INFO;
  const int row0 = (cta >> 4) * 8192 + (cta & 15) * 512;
  uint64_t pol;
  asm volatile("createpolicy.fractional.L2::evict_first.b64 %0, 1.0;" : "=l"(pol));
#pragma unroll 1
  for (int dn = 0; dn < NB * NT; dn++) {
    uint32_t st, bit, it = 0;
    while (true) {
      st = lds32(state);
      const uint32_t fr = st & ((1u << NSLOT) - 1);
      bit = fr & (0u - fr);
      if (bit && (int)(st >> 24) + LIM > dn && (!(st & ST_LOPEN) || fr != bit)) {
        uint32_t old;
        asm volatile("atom.relaxed.cta.shared::cta.and.b32 %0, [%1], %2;" : "=r"(old) : "r"(state), "r"(~bit) : "memory");
        if (old & bit) break;
      }
      __nanosleep(SPN);
      if (++it > (SPIN_LIMIT << 2)) __trap();
    }
    const int slot = __ffs(bit) - 1;
    const bool ret = (dn & 15) >= NT - RB && ((st >> 13) & 31) < ((st & ST_LOPEN) ? RMAX - RL : RMAX);
    const bool l2 = !ret && ((st >> 18) & 31) < L2MAX;
    if (ret || l2) state_add(state, ret ? ST_RET : ST_L2);
    sts8(info + dn, slot | (ret ? 0x80 : 0) | (l2 ? 0x40 : 0));
    const int ahead = dn - (int)(st >> 24);
    const int wd = ahead >= A1_ ? WLOW_ : ahead >= A2_ ? WD : WHI_;
    const int h = 2 * dn;
    const uint32_t fb = bars + 8 * (BAR_FULLD + (h & 63));
    const int row = row0 + (dn >> 4) * 65536 + (dn & 15) * TK;
    const uint32_t dst = sbase + slot * TILE_BYTES;
    mbar_expect_tx(fb, HALF_BYTES);
    mbar_expect_tx(fb + 8, HALF_BYTES);
    if (h >= wd) mbar_wait(bars + 8 * (BAR_FULLD + ((h - wd) & 63)), ((h - wd) >> 6) & 1);
    tma_half(dst, tm, row, 0, fb, pol);
    if (l2) tma_prefetch(tm, row, 0);
    if (h + 1 >= wd) mbar_wait(bars + 8 * (BAR_FULLD + ((h + 1 - wd) & 63)), ((h + 1 - wd) >> 6) & 1);
    tma_half(dst + HALF_BYTES, tm, row, 1, fb + 8, pol);
    if (l2) tma_prefetch(tm, row, 1);
    TL(3, dn);
  }
}

__device__ __forceinline__ void producer_l(char* smem, int cta, const CUtensorMap* tm) {
  const uint32_t sbase = smem_u32(smem);
  const uint32_t bars = sbase + OFF_BAR;
  const uint32_t state = sbase + OFF_MISC;
  const uint32_t info = sbase + OFF_INFO, linfo = info + NB * NT;
  const int row0 = (cta >> 4) * 8192 + (cta & 15) * 512;
  uint64_t pol;
  asm volatile("createpolicy.fractional.L2::evict_first.b64 %0, 1.0;" : "=l"(pol));
  uint32_t lpar = 0;
  uint32_t lq[WL];
#pragma unroll
  for (int i = 0; i < WL; i++) lq[i] = 0;
#pragma unroll 1
  for (int lb = 0; lb < NB; lb++) {
    mbar_wait(bars + 8 * ((lb == NB - 1 ? BAR_P1DONE : BAR_LGO) + lb), 0);
    state_add(state, ST_LOPEN);
#pragma unroll 1
    for (int t = 0; t < NT; t++) {
      const uint32_t inf = lds8(info + lb * NT + t);
      if (inf & 0x80) continue;
      uint32_t bit, it = 0;
      while (true) {
        uint32_t fr = lds32(state) & ((1u << NSLOT) - 1);
        if (fr) {
          bit = 0x80000000u >> __clz(fr);
          uint32_t old;
          asm volatile("atom.relaxed.cta.shared::cta.and.b32 %0, [%1], %2;" : "=r"(old) : "r"(state), "r"(~bit) : "memory");
          if (old & bit) break;
        }
        __nanosleep(SPN);
        if (++it > (SPIN_LIMIT << 2)) __trap();
      }
      const int slot = __ffs(bit) - 1;
      sts8(linfo + lb * NT + t, slot);
      const int bi = (lb & 1) * NT + t;
      const uint32_t fb = bars + 8 * (BAR_FULLL + 2 * bi);
      const int row = row0 + lb * 65536 + t * TK;
      mbar_expect_tx(fb, HALF_BYTES);
      mbar_expect_tx(fb + 8, HALF_BYTES);
#pragma unroll
      for (int part = 0; part < 2; part++) {
        if (lq[0] && lb < NB - 1) mbar_wait(bars + 8 * (lq[0] & 0xff), (lq[0] >> 8) & 1);
        tma_half(sbase + slot * TILE_BYTES + part * HALF_BYTES, tm, row, part, fb + 8 * part, pol);
#pragma unroll
        for (int i = 0; i + 1 < WL; i++) lq[i] = lq[i + 1];
        lq[WL - 1] = (BAR_FULLL + 2 * bi + part) | (((lpar >> bi) & 1) << 8) | 0x200;
      }
      if (inf & 0x40) state_add(state, 0u - ST_L2);
      TL(3, 128 + lb * 16 + t);
      lpar ^= 1u << bi;
    }
    state_add(state, 0u - ST_LOPEN);
  }
}

__global__ void __launch_bounds__(NTHREADS, 1)
    fused_kernel(const __grid_constant__ CUtensorMap tm, uint32_t koff, const __nv_bfloat16* __restrict__ x,
                 const __nv_bfloat16* __restrict__ wq,
                 const __nv_bfloat16* __restrict__ wo, const __nv_bfloat16* __restrict__ w1,
                 const __nv_bfloat16* __restrict__ w2, __nv_bfloat16* __restrict__ out) {
  extern __shared__ __align__(1024) char smem[];
  const int tid = threadIdx.x, warp = tid >> 5, lane = tid & 31, cta = blockIdx.x;
  if (tid == 0) {
    const uint32_t sbase = smem_u32(smem);
    if (sbase & 1023) __trap();
    const uint32_t bars = sbase + OFF_BAR;
    for (int i = 0; i < 128; i++) mbar_init(bars + 8 * i, 1);
    for (int i = 0; i < 8; i++) {
      mbar_init(bars + 8 * (BAR_P1DONE + i), NW1);
      mbar_init(bars + 8 * (BAR_P2DONE + i), NW2);
      mbar_init(bars + 8 * (BAR_QGO + i), 1);
      mbar_init(bars + 8 * (BAR_LGO + i), NW2);
    }
    mbar_init(bars + 8 * BAR_Q1, NW1);
    uint32_t* misc = (uint32_t*)(smem + OFF_MISC);
    misc[0] = (1u << NSLOT) - 1;
    misc[1] = *(volatile unsigned*)&g_epoch;
    asm volatile("fence.mbarrier_init.release.cluster;" ::: "memory");
  }
  __syncthreads();
  const unsigned epoch = ((const uint32_t*)(smem + OFF_MISC))[1];
  const uint32_t tag = epoch + 1;
  if (warp < 8) {
    asm volatile("setmaxnreg.inc.sync.aligned.u32 152;");
    chain_role(smem, tid, cta, tag, x, wq, wo, w1, w2, out);
    if (cta == 1 && tid == 0) *(volatile unsigned*)&g_epoch = epoch + 1;
  } else if (warp < 12) {
    asm volatile("setmaxnreg.dec.sync.aligned.u32 104;");
    if (warp < 8 + NW1) {
      attn_role<0, NW1>(smem, warp - 8, lane, cta, tag, koff);
    } else if (warp == 10) {
      if (lane == 0) producer_d(smem, cta, &tm);
    } else if (lane == 0) {
      producer_l(smem, cta, &tm);
    }
  } else {
    asm volatile("setmaxnreg.dec.sync.aligned.u32 104;");
    attn_role<1, NW2>(smem, warp - 12, lane, cta, tag, koff);
  }
}

typedef CUresult (*EncodeFn)(CUtensorMap*, CUtensorMapDataType, cuuint32_t, void*, const cuuint64_t*, const cuuint64_t*,
                             const cuuint32_t*, const cuuint32_t*, CUtensorMapInterleave, CUtensorMapSwizzle,
                             CUtensorMapL2promotion, CUtensorMapFloatOOBfill);

static_assert(SMEM_BYTES <= 232448, "smem");
}

extern "C" void kernel_launch(void* const* d_in, const int* in_sizes, int n_in, void* d_out, int out_size) {
  static EncodeFn enc = nullptr;
  if (!enc) {
    void* fn = nullptr;
    cudaDriverEntryPointQueryResult qr;
    cudaGetDriverEntryPoint("cuTensorMapEncodeTiled", &fn, cudaEnableDefault, &qr);
    enc = (EncodeFn)fn;
    cudaFuncSetAttribute(fused_kernel, cudaFuncAttributeMaxDynamicSharedMemorySize, SMEM_BYTES);
  }
  const __nv_bfloat16* x = (const __nv_bfloat16*)d_in[0];
  const __nv_bfloat16* kc = (const __nv_bfloat16*)d_in[1];
  const __nv_bfloat16* vc = (const __nv_bfloat16*)d_in[2];
  const __nv_bfloat16* wq = (const __nv_bfloat16*)d_in[3];
  const __nv_bfloat16* wo = (const __nv_bfloat16*)d_in[4];
  const __nv_bfloat16* w1 = (const __nv_bfloat16*)d_in[6];
  const __nv_bfloat16* w2 = (const __nv_bfloat16*)d_in[7];
  const bool kfirst = (const char*)kc < (const char*)vc;
  const char* lo = kfirst ? (const char*)kc : (const char*)vc;
  const char* hi = kfirst ? (const char*)vc : (const char*)kc;
  CUtensorMap tm;
  cuuint64_t dims[4] = {64, (cuuint64_t)8 * 8 * 8192, 2, 2};
  cuuint64_t strides[3] = {256, 128, (cuuint64_t)(hi - lo)};
  cuuint32_t box[4] = {64, TK, 2, 1};
  cuuint32_t es[4] = {1, 1, 1, 1};
  enc(&tm, CU_TENSOR_MAP_DATA_TYPE_BFLOAT16, 4, (void*)lo, dims, strides, box, es, CU_TENSOR_MAP_INTERLEAVE_NONE,
      CU_TENSOR_MAP_SWIZZLE_128B, CU_TENSOR_MAP_L2_PROMOTION_NONE, CU_TENSOR_MAP_FLOAT_OOB_FILL_NONE);
  fused_kernel<<<128, NTHREADS, SMEM_BYTES>>>(tm, kfirst ? 0u : (uint32_t)HALF_BYTES, x, wq, wo, w1, w2,
                                              (__nv_bfloat16*)d_out);
}
```
